```python
import torch

def _softmax(x, axis=-1):
    return torch.softmax(x, dim=axis)
def _gelu(x):
    return torch.nn.functional.gelu(x, approximate="tanh")
def _silu(x):
    return torch.nn.functional.silu(x)
def _sigmoid(x):
    return torch.sigmoid(x)
def _layernorm(x, axis=-1, eps=1e-5):
    m = x.mean(dim=axis, keepdim=True)
    v = x.var(dim=axis, keepdim=True, unbiased=False)
    return (x - m) / torch.sqrt(v + eps)
def _scatter_add(tgt, idx, src, axis=0):
    return tgt.clone().index_add_(axis, idx, src)
def _segment_sum(src, seg, n):
    out = torch.zeros((n,) + src.shape[1:], dtype=src.dtype)
    return out.index_add_(0, seg, src)
def _pad(x, pw):
    flat = tuple(v for pair in reversed(pw) for v in pair)
    return torch.nn.functional.pad(x, flat)

kernel_name = 'sequential_preLN__compressed_kv_cla__glu_gated_glu__decode'

def setup_inputs():

    _w = (lambda a: (lambda t: t.to(torch.bfloat16) if t.is_floating_point() else t)(torch.as_tensor(a)))
    def _A_setup():
        B, H, Sq, Sk, D, M = 1, 16, 1, 8192, 256, 448
        Dc = 4 * D
        return {
            "x": _w((lambda *s: torch.randn(*s, dtype=torch.bfloat16) * 0.05)(B, Sq, M)),
            "c_kv": _w((lambda *s: torch.randn(*s, dtype=torch.bfloat16) * 0.4)(B, Sk, Dc)),
            "w_q": _w((lambda *s: torch.randn(*s, dtype=torch.bfloat16) * 3.2)(M, H, D) * (M ** -0.5)),
            "w_uk": _w((lambda *s: torch.randn(*s, dtype=torch.bfloat16) * 3.2)(Dc, H, D) * (Dc ** -0.5)),
            "w_uv": _w((lambda *s: torch.randn(*s, dtype=torch.bfloat16) * 0.4)(Dc, H, D) * (Dc ** -0.5)),
            "w_o": _w((lambda *s: torch.randn(*s, dtype=torch.bfloat16) * 0.4)(H, D, M) * ((H * D) ** -0.5)),
        }
    _A_in = _A_setup()

    def _B_setup():
        B, S, D, F = 1, 1, 448, 1792
        return {
            "x": _w((lambda *s: torch.randn(*s, dtype=torch.bfloat16) * 0.05)(B, S, D)),
            "w_gate": _w((lambda *s: torch.randn(*s, dtype=torch.bfloat16) * 0.05)(D, F)),
            "w_up": _w((lambda *s: torch.randn(*s, dtype=torch.bfloat16) * 0.05)(D, F)),
            "w_down": _w((lambda *s: torch.randn(*s, dtype=torch.bfloat16) * 0.05)(F, D)),
        }
    _B_in = _B_setup()

    return {
        "A_x": _A_in["x"],
        "A_c_kv": _A_in["c_kv"],
        "A_w_q": _A_in["w_q"],
        "A_w_uk": _A_in["w_uk"],
        "A_w_uv": _A_in["w_uv"],
        "A_w_o": _A_in["w_o"],
        "B_x": _B_in["x"],
        "B_w_gate": _B_in["w_gate"],
        "B_w_up": _B_in["w_up"],
        "B_w_down": _B_in["w_down"],
    }

def reference(A_x, A_c_kv, A_w_q, A_w_uk, A_w_uv, A_w_o, B_x, B_w_gate, B_w_up, B_w_down):
    def _A_ref(x, c_kv, w_q, w_uk, w_uv, w_o):
        B, Sq, M = x.shape[0], x.shape[1], x.shape[2]
        Sk = c_kv.shape[1]
        H, D = w_q.shape[1], w_q.shape[2]
        q = torch.einsum("bqm,mhd->bhqd", x, w_q)
        k = torch.einsum("bkc,chd->bhkd", c_kv, w_uk)
        v = torch.einsum("bkc,chd->bhkd", c_kv, w_uv)
        scores = torch.einsum("bhqd,bhkd->bhqk", q, k) * (D ** -0.5)
        off = Sk - Sq
        qi = torch.arange(Sq)[:, None]
        kj = torch.arange(Sk)[None, :]
        cmask = kj <= (qi + off)
        scores = torch.where(cmask[None, None], scores, -1e9)
        p = _softmax(scores, axis=-1)
        ctx = torch.einsum("bhqk,bhkd->bhqd", p, v)
        return torch.einsum("bhqd,hdm->bqm", ctx, w_o)

    def _B_ref(x, w_gate, w_up, w_down):
        g = torch.einsum("bsd,df->bsf", x, w_gate)
        u = torch.einsum("bsd,df->bsf", x, w_up)
        h = _sigmoid(g) * u
        return torch.einsum("bsf,fd->bsd", h, w_down)

    x = A_x
    h = x + _A_ref(_layernorm(x, axis=-1), A_c_kv, A_w_q, A_w_uk, A_w_uv, A_w_o)
    h2 = h + _B_ref(_layernorm(h, axis=-1), B_w_gate, B_w_up, B_w_down)
    return h2
```

```cpp
#include <cuda_runtime.h>
#include <cuda_bf16.h>
#include <cuda.h>
#include <stdint.h>
#include <limits.h>

namespace {

constexpr int NC_MAX = 32, NC_MIN = 29;
constexpr int NTHR = 512;

constexpr uint32_t UNIT = 8192;
constexpr uint32_t OFF_CKV = 0;
constexpr uint32_t OFF_WA = 18 * UNIT;
constexpr uint32_t OFF_X = OFF_WA + 9 * UNIT;
constexpr uint32_t OFF_SLOT = OFF_X;
constexpr uint32_t OFF_PBUF = OFF_X + 3 * 2048;
constexpr uint32_t PSTRIDE = 1088;
constexpr uint32_t OFF_BAR = OFF_PBUF + 4 * PSTRIDE;
constexpr uint32_t OFF_WGT = OFF_BAR + 40 * 8;
constexpr uint32_t OFF_REF = OFF_WGT + 272;
constexpr uint32_t SMEM_BYTES = OFF_REF + 48;
constexpr uint32_t OFF_QST = OFF_PBUF;
constexpr uint32_t OFF_TILE = OFF_X;
constexpr uint32_t OFF_CTX = OFF_X + 9216;
constexpr uint32_t OFF_AFR = OFF_X + 9728;
constexpr uint32_t OFF_H = OFF_X;
constexpr uint32_t OFF_GU = OFF_X + 1024;
static_assert(OFF_AFR + 576 <= OFF_BAR, "staging overflow");
static_assert(SMEM_BYTES + 128 <= 232448, "smem overflow");

enum { B_S0 = 26, B_P0 = 29, B_H = 33, B_GU = 34, G_P1 = 35, G_QA = 36, NBARS = 37 };
constexpr uint32_t OFF_PVC = OFF_BAR + 38 * 8;

struct __align__(64) Params {
    CUtensorMap wq, wuk, ckv, wuv, wo, wg, wu, wd;
    const __nv_bfloat16* x;
    __nv_bfloat16* out;
    int NC;
    int W;
    uint2 tab[4 * NC_MAX];
};

constexpr uint32_t MB1 = 0;
constexpr uint32_t MB2 = MB1 + 112 * 1024;
constexpr uint32_t MB3 = MB2 + 32768;
constexpr uint32_t MBM = MB3 + 1024 * 1024;
constexpr uint32_t MB4 = MBM + 4096;
constexpr uint32_t MB5 = MB4 + 16 * 12 * 1024;
constexpr uint32_t MB6 = MB5 + 16 * 1792;
constexpr uint32_t MB_SET = (MB6 + 4 * 28 * 28 * 16 + 1023) / 1024 * 1024;
__device__ __align__(1024) unsigned char g_mb[2 * MB_SET];
__device__ unsigned g_epoch;
#define TRACE(i) do {} while (0)

constexpr int SPIN_LIMIT = 1 << 18;

__device__ __forceinline__ void mbar_init(uint32_t b, uint32_t c) {
    asm volatile("mbarrier.init.shared::cta.b64 [%0], %1;" ::"r"(b), "r"(c) : "memory");
}
__device__ __forceinline__ void mbar_expect(uint32_t b, uint32_t bytes) {
    asm volatile("mbarrier.arrive.expect_tx.shared::cta.b64 _, [%0], %1;" ::"r"(b), "r"(bytes) : "memory");
}
__device__ __forceinline__ void mbar_arrive(uint32_t b) {
    asm volatile("mbarrier.arrive.shared::cta.b64 _, [%0];" ::"r"(b) : "memory");
}
__device__ __forceinline__ bool mbar_try(uint32_t b, uint32_t ph) {
    uint32_t ok;
    asm volatile("{.reg .pred p; mbarrier.try_wait.parity.shared::cta.b64 p, [%1], %2; selp.u32 %0,1,0,p;}"
                 : "=r"(ok) : "r"(b), "r"(ph) : "memory");
    return ok;
}
__device__ __forceinline__ bool mbar_try_cl(uint32_t b, uint32_t ph) {
    uint32_t ok;
    asm volatile("{.reg .pred p; mbarrier.try_wait.parity.acquire.cluster.shared::cta.b64 p, [%1], %2; selp.u32 %0,1,0,p;}"
                 : "=r"(ok) : "r"(b), "r"(ph) : "memory");
    return ok;
}
__device__ __forceinline__ void mbar_wait(uint32_t b, uint32_t ph) {
#pragma unroll 1
    for (int i = 0; i < SPIN_LIMIT; i++)
        if (mbar_try(b, ph)) return;
}
__device__ __forceinline__ void mbar_wait_cl(uint32_t b, uint32_t ph) {
#pragma unroll 1
    for (int i = 0; i < SPIN_LIMIT; i++)
        if (mbar_try_cl(b, ph)) return;
}
__device__ __forceinline__ void tma2p(uint32_t dst, const CUtensorMap* m, int x, int y, uint32_t bar, unsigned long long pol) {
    asm volatile("cp.async.bulk.tensor.2d.shared::cluster.global.mbarrier::complete_tx::bytes.L2::cache_hint [%0], [%1, {%3, %4}], [%2], %5;"
                 ::"r"(dst), "l"(m), "r"(bar), "r"(x), "r"(y), "l"(pol) : "memory");
}
__device__ __forceinline__ void tma3p(uint32_t dst, const CUtensorMap* m, int x, int y, int z, uint32_t bar, unsigned long long pol) {
    asm volatile("cp.async.bulk.tensor.3d.shared::cluster.global.mbarrier::complete_tx::bytes.L2::cache_hint [%0], [%1, {%3, %4, %5}], [%2], %6;"
                 ::"r"(dst), "l"(m), "r"(bar), "r"(x), "r"(y), "r"(z), "l"(pol) : "memory");
}
__device__ __forceinline__ uint32_t mapa(uint32_t a, uint32_t rank) {
    uint32_t r;
    asm("mapa.shared::cluster.u32 %0, %1, %2;" : "=r"(r) : "r"(a), "r"(rank));
    return r;
}
__device__ __forceinline__ void st_async_v4(uint32_t a, uint32_t x, uint32_t y, uint32_t z, uint32_t w, uint32_t bar) {
    asm volatile("st.async.weak.shared::cluster.mbarrier::complete_tx::bytes.v4.b32 [%0], {%1,%2,%3,%4}, [%5];"
                 ::"r"(a), "r"(x), "r"(y), "r"(z), "r"(w), "r"(bar) : "memory");
}
__device__ __forceinline__ void st_async_b32(uint32_t a, uint32_t x, uint32_t bar) {
    asm volatile("st.async.weak.shared::cluster.mbarrier::complete_tx::bytes.b32 [%0], %1, [%2];"
                 ::"r"(a), "r"(x), "r"(bar) : "memory");
}
__device__ __forceinline__ void ldsm4(uint32_t a, uint32_t& r0, uint32_t& r1, uint32_t& r2, uint32_t& r3) {
    asm volatile("ldmatrix.sync.aligned.m8n8.x4.shared.b16 {%0,%1,%2,%3}, [%4];"
                 : "=r"(r0), "=r"(r1), "=r"(r2), "=r"(r3) : "r"(a) : "memory");
}
__device__ __forceinline__ void ldsm4t(uint32_t a, uint32_t& r0, uint32_t& r1, uint32_t& r2, uint32_t& r3) {
    asm volatile("ldmatrix.sync.aligned.m8n8.x4.trans.shared.b16 {%0,%1,%2,%3}, [%4];"
                 : "=r"(r0), "=r"(r1), "=r"(r2), "=r"(r3) : "r"(a) : "memory");
}
__device__ __forceinline__ void mma16816(float (&c)[4], uint32_t a0, uint32_t a1, uint32_t a2, uint32_t a3, uint32_t b0, uint32_t b1) {
    asm("mma.sync.aligned.m16n8k16.row.col.f32.bf16.bf16.f32 {%0,%1,%2,%3}, {%4,%5,%6,%7}, {%8,%9}, {%0,%1,%2,%3};"
                 : "+f"(c[0]), "+f"(c[1]), "+f"(c[2]), "+f"(c[3]) : "r"(a0), "r"(a1), "r"(a2), "r"(a3), "r"(b0), "r"(b1));
}
__device__ __forceinline__ uint4 lds128(uint32_t a) {
    uint4 v;
    asm volatile("ld.shared.v4.u32 {%0,%1,%2,%3}, [%4];" : "=r"(v.x), "=r"(v.y), "=r"(v.z), "=r"(v.w) : "r"(a) : "memory");
    return v;
}
__device__ __forceinline__ uint32_t lds32(uint32_t a) {
    uint32_t v;
    asm volatile("ld.shared.u32 %0, [%1];" : "=r"(v) : "r"(a) : "memory");
    return v;
}
__device__ __forceinline__ uint32_t lds32_acq(uint32_t a) {
    uint32_t v;
    asm volatile("ld.acquire.cta.shared.u32 %0, [%1];" : "=r"(v) : "r"(a) : "memory");
    return v;
}
__device__ __forceinline__ void sts32_rel(uint32_t a, uint32_t v) {
    asm volatile("st.release.cta.shared.u32 [%0], %1;" ::"r"(a), "r"(v) : "memory");
}
__device__ __forceinline__ void red_add_rel(uint32_t a, uint32_t v) {
    asm volatile("red.release.cta.shared.add.u32 [%0], %1;" ::"r"(a), "r"(v) : "memory");
}
__device__ __forceinline__ void pv_wait(uint32_t pvc, int k) {
#pragma unroll 1
    for (int it = 0; it < SPIN_LIMIT * 8; it++)
        if ((int)lds32_acq(pvc + (k & 3) * 4) >= 8 * ((k >> 2) + 1)) return;
}
__device__ __forceinline__ void sts128(uint32_t a, uint4 v) {
    asm volatile("st.shared.v4.u32 [%0], {%1,%2,%3,%4};" ::"r"(a), "r"(v.x), "r"(v.y), "r"(v.z), "r"(v.w) : "memory");
}
__device__ __forceinline__ void sts32(uint32_t a, uint32_t v) {
    asm volatile("st.shared.u32 [%0], %1;" ::"r"(a), "r"(v) : "memory");
}
__device__ __forceinline__ void sts16(uint32_t a, uint16_t v) {
    asm volatile("st.shared.u16 [%0], %1;" ::"r"(a), "h"(v) : "memory");
}
__device__ __forceinline__ void bar_sync(int id, int n) {
    asm volatile("bar.sync %0, %1;" ::"r"(id), "r"(n) : "memory");
}
__device__ __forceinline__ float bf16r(float v) { return __bfloat162float(__float2bfloat16_rn(v)); }
__device__ __forceinline__ uint32_t pack2(float lo, float hi) {
    __nv_bfloat162 t = __floats2bfloat162_rn(lo, hi);
    return *reinterpret_cast<uint32_t*>(&t);
}
__device__ __forceinline__ float bflo(uint32_t w) { return __uint_as_float(w << 16); }
__device__ __forceinline__ float bfhi(uint32_t w) { return __uint_as_float(w & 0xffff0000u); }
__device__ __forceinline__ float ex2(float x) {
    float y;
    asm("ex2.approx.ftz.f32 %0, %1;" : "=f"(y) : "f"(x));
    return y;
}
__device__ __forceinline__ uint32_t ldg_early(const uint32_t* p) {
    uint32_t v;
    asm volatile("ld.global.nc.u32 %0, [%1];" : "=r"(v) : "l"(p));
    return v;
}

__device__ __forceinline__ void mb_st2(unsigned char* p, uint32_t a, uint32_t b) {
    asm volatile("st.relaxed.gpu.global.v2.u32 [%0], {%1,%2};" ::"l"(p), "r"(a), "r"(b) : "memory");
}
__device__ __forceinline__ void mb_put2(unsigned char* p, uint32_t a, uint32_t b) { mb_st2(p, a == 0u ? 0x80000000u : a, b); }
__device__ __forceinline__ void mb_put2f(unsigned char* p, float a, float b) { mb_put2(p, __float_as_uint(a), __float_as_uint(b)); }
__device__ __forceinline__ void mb_clear2(uint32_t off) {
    mb_st2(g_mb + off, 0u, 0u);
    mb_st2(g_mb + MB_SET + off, 0u, 0u);
}
__device__ __forceinline__ uint4 mb_ld4(const unsigned char* p) {
    uint4 v;
    asm volatile("ld.relaxed.gpu.global.v4.u32 {%0,%1,%2,%3}, [%4];" : "=r"(v.x), "=r"(v.y), "=r"(v.z), "=r"(v.w) : "l"(p) : "memory");
    return v;
}
template <int N, int STRIDE>
__device__ __forceinline__ void mb_poll(const unsigned char* p, int n, uint4 (&v)[N]) {
#pragma unroll
    for (int i = 0; i < N; i++) v[i] = make_uint4(0, 0, 0, 0);
#pragma unroll 1
    for (int it = 0; it < SPIN_LIMIT; it++) {
        uint32_t m = 0xffffffffu;
#pragma unroll
        for (int i = 0; i < N; i++)
            if (i < n) v[i] = mb_ld4(p + i * STRIDE);
#pragma unroll
        for (int i = 0; i < N; i++)
            if (i < n) m = min(m, min(v[i].x, v[i].z));
        if (m != 0u) break;
    }
}

__device__ __forceinline__ void ln_stats(const float (&v)[14], float& mb, float& den) {
    float s = 0.f;
#pragma unroll
    for (int i = 0; i < 14; i++) s += v[i];
#pragma unroll
    for (int o = 16; o; o >>= 1) s += __shfl_xor_sync(~0u, s, o);
    const float mean = s * (1.f / 448.f);
    float q = 0.f;
#pragma unroll
    for (int i = 0; i < 14; i++) { const float d = v[i] - mean; q += d * d; }
#pragma unroll
    for (int o = 16; o; o >>= 1) q += __shfl_xor_sync(~0u, q, o);
    mb = bf16r(mean);
    den = bf16r(__fsqrt_rn(bf16r(bf16r(q * (1.f / 448.f)) + 1e-5f)));
}
__device__ __forceinline__ float ln_apply(float v, float mb, float den) { return __fdiv_rn(bf16r(v - mb), den); }
__device__ __forceinline__ float ln_apply_r(float v, float mb, float rden) { return bf16r(v - mb) * rden; }

__device__ __forceinline__ uint32_t frag_off(int w) {
    const int s = w >> 3, half = (w >> 2) & 1, t = w & 3;
    return (uint32_t)((((s >> 1) * 4 + t) * 4 + (s & 1) * 2 + half) * 4);
}
__device__ __forceinline__ int f2o(float f) { const int i = __float_as_int(f); return i ^ ((i >> 31) & 0x7fffffff); }
__device__ __forceinline__ float o2f(int i) { return __int_as_float(i ^ ((i >> 31) & 0x7fffffff)); }

__device__ __forceinline__ void combine_unit(uint32_t SB, const unsigned char* src, int ul, bool active, bool isA, int NC, int lane) {
    uint4 v[2];
    mb_poll<2, 512>(src + lane * 16, active ? ((16 + (lane >> 1) < NC) ? 2 : 1) : 0, v);
    const uint32_t tile = SB + OFF_TILE + ul * 1024;
    sts128(tile + lane * 16, v[0]);
    sts128(tile + 512 + lane * 16, v[1]);
    bar_sync(2, 352);
    const int t = lane & 3;
    const uint4 w0 = lds128(SB + OFF_WGT + (isA ? 0 : 128) + t * 16), w1 = lds128(SB + OFF_WGT + (isA ? 64 : 192) + t * 16);
    uint32_t b[8];
    const uint32_t ts = tile + ((lane & 7) + (lane & 8)) * 32 + (lane >> 4) * 16;
    ldsm4t(ts, b[0], b[1], b[2], b[3]);
    ldsm4t(ts + 512, b[4], b[5], b[6], b[7]);
    float c0[4] = {}, c1[4] = {}, c2[4] = {}, c3[4] = {};
    mma16816(c0, w0.x, w0.y, w0.z, w0.w, b[0], b[1]);
    mma16816(c1, w0.x, w0.y, w0.z, w0.w, b[2], b[3]);
    mma16816(c2, w1.x, w1.y, w1.z, w1.w, b[4], b[5]);
    mma16816(c3, w1.x, w1.y, w1.z, w1.w, b[6], b[7]);
    const float v0 = (c0[0] + c0[2]) + (c2[0] + c2[2]), v1 = (c0[1] + c0[3]) + (c2[1] + c2[3]);
    const float v2 = (c1[0] + c1[2]) + (c3[0] + c3[2]), v3 = (c1[1] + c1[3]) + (c3[1] + c3[3]);
    const uint32_t a0 = pack2(v0, v1), a2 = pack2(v2, v3);
    const uint32_t a1 = pack2(v0 - bflo(a0), v1 - bfhi(a0)), a3 = pack2(v2 - bflo(a2), v3 - bfhi(a2));
    if (lane < 4) sts128(SB + OFF_AFR + ul * 64 + t * 16, make_uint4(a0, a1, a2, a3));
}

__global__ void __launch_bounds__(NTHR, 1) fused_kernel(const __grid_constant__ Params P) {
    extern __shared__ __align__(1024) unsigned char smem_raw[];
    const uint32_t SB = (uint32_t)__cvta_generic_to_shared(smem_raw);
    const int tid = threadIdx.x, warp = tid >> 5, lane = tid & 31;
    const int g = lane >> 2, t = lane & 3;
    const int cta = blockIdx.x, j = cta >> 2, r = cta & 3;
    const uint2 tab = P.tab[cta];
    const int u0 = tab.x & 1023, nu = (tab.x >> 10) & 15, k0 = (tab.x >> 14) & 511, nk = (tab.x >> 23) & 31;
    const int h7 = tab.y & 15, mb7 = (tab.y >> 4) & 7;
    const bool full = cta < 112;
    const int nug = (nu + 1) >> 1, nb = (nk + 1) >> 1;
    const int g_uk = full ? 2 : 0, g_kv = g_uk + nug, g_uv = g_kv + nb, g_wo = g_uv + nug, g_gu = g_wo + 2, g_wd = g_gu + 2;
    auto BAR = [&](int i) -> uint32_t { return SB + OFF_BAR + 8 * i; };

    if (warp == 11) {
        const int W1 = P.W & 15, W2 = (P.W >> 4) & 15, W3 = (P.W >> 8) & 15, ngroups = full ? g_wd + 1 : g_wo;
        int done = 0;
        unsigned long long pol;
        asm volatile("createpolicy.fractional.L2::evict_first.b64 %0, 1.0;" : "=l"(pol));
        if (lane < 8) asm volatile("prefetch.tensormap [%0];" ::"l"(reinterpret_cast<const char*>(&P) + lane * 128) : "memory");
        if (lane == 0) {
            mbar_init(BAR(0), 1);
            mbar_init(BAR(1), 1);
            mbar_init(BAR(2), 1);
            mbar_init(BAR(3), 1);
            asm volatile("fence.mbarrier_init.release.cluster;" ::: "memory");
        }
        __syncwarp();
#pragma unroll 1
        for (int gi = 0; gi < ngroups; gi++) {
            if (gi == min(W1, 4)) {
                __syncthreads();
                asm volatile("barrier.cluster.arrive.relaxed.aligned;" ::: "memory");
            }
            const CUtensorMap* map;
            uint32_t dst, dstep = UNIT;
            int n = 2, x0 = 0, y0, z0 = -1, x1 = 0, y1, z1 = 0, gate = -1, pvgate = 0;
            if (gi < g_uk) {
                map = &P.wq; dst = OFF_CKV + (14 + 2 * gi) * UNIT;
                y0 = mb7 * 64 + gi * 32; y1 = y0 + 16; z0 = z1 = h7 * 4;
            } else if (gi < g_kv || (gi >= g_uv && gi < g_wo)) {
                const bool uv = gi >= g_uv;
                const int i0 = 2 * (gi - (uv ? g_uv : g_uk)), u = u0 + i0;
                if (gi == g_uv) gate = G_QA;
                map = uv ? &P.wuv : &P.wuk; dst = OFF_WA + i0 * UNIT; n = min(2, nu - i0);
                y0 = (u & 63) * 16; z0 = (u >> 6) * 4; y1 = ((u + 1) & 63) * 16; z1 = ((u + 1) >> 6) * 4;
            } else if (gi < g_uv) {
                const int b = gi - g_kv;
                if (b == 7 && full) gate = G_P1;
                map = &P.ckv; dst = OFF_CKV + 2 * b * UNIT; n = min(2, nk - 2 * b);
                y0 = (k0 + 2 * b) * 16; y1 = y0 + 16; z0 = z1 = r * 4;
            } else if (gi < g_gu) {
                const int i = gi - g_wo;
                pvgate = 1;
                map = &P.wo; dst = OFF_CKV + 2 * i * UNIT;
                x0 = x1 = mb7 * 64; y0 = h7 * 256 + i * 128; y1 = y0 + 64;
            } else if (gi < g_wd) {
                const int i = gi - g_gu;
                pvgate = 3;
                map = (r & 1) ? &P.wu : &P.wg; dst = OFF_CKV + 4 * UNIT + i * 14336; n = 1; dstep = 14336;
                x0 = j * 64; y0 = (r >> 1) * 224 + i * 112; y1 = 0;
            } else {
                pvgate = 4;
                map = &P.wd; dst = OFF_CKV + 8 * UNIT;
                x0 = r * 112; x1 = x0 + 64; y0 = y1 = j * 64;
            }
            if (gate >= 0) mbar_wait(BAR(gate), 0);
            if (pvgate) pv_wait(SB + OFF_PVC, pvgate);
            {
                const int W = gi < g_kv ? W1 : gi < g_uv ? W2 : W3;
#pragma unroll 1
                for (; done <= gi - W; done++) mbar_wait(BAR(done), 0);
            }
            if (lane == 0) {
                const uint32_t bar = BAR(gi);
                mbar_expect(bar, n * dstep);
                if (z0 >= 0) {
                    tma3p(SB + dst, map, 0, y0, z0, bar, pol);
                    if (n > 1) tma3p(SB + dst + UNIT, map, 0, y1, z1, bar, pol);
                } else {
                    tma2p(SB + dst, map, x0, y0, bar, pol);
                    if (n > 1) tma2p(SB + dst + UNIT, map, x1, y1, bar, pol);
                }
                if (gi == g_kv) TRACE(15);
                if (gi == g_uv) TRACE(19);
                if (gi == g_wo) TRACE(20);
            }
            __syncwarp();
        }
        if (lane == 0) TRACE(31);
        asm volatile("barrier.cluster.wait.acquire.aligned;" ::: "memory");
        return;
    }

    uint32_t epoch, xr[7], xa[8], xw0, xw1;
    {
        const uint32_t* x32 = reinterpret_cast<const uint32_t*>(P.x);
        asm volatile("ld.relaxed.gpu.global.u32 %0, [%1];" : "=r"(epoch) : "l"(&g_epoch) : "memory");
#pragma unroll
        for (int i = 0; i < 7; i++) xr[i] = ldg_early(x32 + lane + 32 * i);
#pragma unroll
        for (int i = 0; i < 8; i++) xa[i] = ldg_early(x32 + mb7 * 32 + (i >> 1) * 8 + (i & 1) * 4 + t);
        xw0 = ldg_early(x32 + r * 56 + 2 * min(lane, 27));
        xw1 = ldg_early(x32 + r * 56 + 2 * min(lane, 27) + 1);
    }
    if (lane == 0) {
#pragma unroll 1
        for (int i = 4 + (warp > 11 ? warp - 1 : warp); i < NBARS; i += 15) mbar_init(BAR(i), i == G_P1 ? 8 : i == G_QA ? 4 : 1);
        if (warp >= 8 && warp < 11) sts32(SB + OFF_WGT + 260 + (warp - 8) * 4, 0);
        if (warp == 12) sts128(SB + OFF_PVC, make_uint4(0, 0, 0, 0));
        asm volatile("fence.mbarrier_init.release.cluster;" ::: "memory");
    }
    __syncthreads();
    asm volatile("barrier.cluster.arrive.relaxed.aligned;" ::: "memory");
    const int NC = P.NC;
    const int hA = u0 >> 6, hB = (u0 + nu - 1) >> 6;

    if (warp >= 12) {
        const int nt = warp - 12;
        const uint32_t s_dst = mapa(SB + OFF_SLOT + r * 512 + (nt * 2 + (g >> 2)) * 64 + t * 16, g & 3);
        const uint32_t s_bar = mapa(BAR(B_S0), g & 3);
        const int srow = (nt & 1) * 8 + (lane & 7);
        const uint32_t s_src0 = SB + OFF_CKV + (nt >> 1) * UNIT + srow * 128 + (((lane >> 3) ^ (srow & 7)) << 4);
        const uint32_t s_src1 = SB + OFF_CKV + (nt >> 1) * UNIT + srow * 128 + (((4 + (lane >> 3)) ^ (srow & 7)) << 4);
        asm volatile("barrier.cluster.wait.acquire.aligned;" ::: "memory");
        bar_sync(6, 384);
        uint32_t qa[16][4];
#pragma unroll
        for (int s = 0; s < 16; s++) {
            const uint4 q = lds128(SB + OFF_WA + s * 512 + lane * 16);
            qa[s][0] = q.x; qa[s][1] = q.y; qa[s][2] = q.z; qa[s][3] = q.w;
        }
        __syncwarp();
        if (lane == 0) mbar_arrive(BAR(G_QA));
        const int nbs = (nk - (nt >> 1) + 1) >> 1;
        int sb = 0;
#pragma unroll 1
        for (int b = 0; b < nbs; b++) {
            mbar_wait(BAR(g_kv + b), 0);
            float c0[4] = {}, c1[4] = {}, c2[4] = {}, c3[4] = {};
#pragma unroll
            for (int i = 0; i < 4; i++) {
                uint32_t b0, b1, b2, b3, b4, b5, b6, b7;
                ldsm4(s_src0 + 2 * b * UNIT + i * 2048, b0, b1, b2, b3);
                ldsm4(s_src1 + 2 * b * UNIT + i * 2048, b4, b5, b6, b7);
                mma16816(c0, qa[4 * i][0], qa[4 * i][1], qa[4 * i][2], qa[4 * i][3], b0, b1);
                mma16816(c1, qa[4 * i + 1][0], qa[4 * i + 1][1], qa[4 * i + 1][2], qa[4 * i + 1][3], b2, b3);
                mma16816(c2, qa[4 * i + 2][0], qa[4 * i + 2][1], qa[4 * i + 2][2], qa[4 * i + 2][3], b4, b5);
                mma16816(c3, qa[4 * i + 3][0], qa[4 * i + 3][1], qa[4 * i + 3][2], qa[4 * i + 3][3], b6, b7);
            }
            if (b >= 3) pv_wait(SB + OFF_PVC, b - 3);
            st_async_v4(s_dst + sb * 2048, __float_as_uint((c0[0] + c1[0]) + (c2[0] + c3[0])),
                        __float_as_uint((c0[1] + c1[1]) + (c2[1] + c3[1])), __float_as_uint((c0[2] + c1[2]) + (c2[2] + c3[2])),
                        __float_as_uint((c0[3] + c1[3]) + (c2[3] + c3[3])), s_bar + sb * 8);
            if (++sb == 3) sb = 0;
        }
        return;
    }
    if (warp >= 8) {
        const int sb = warp - 8, nt = lane >> 3, gg = (lane >> 2) & 1;
        if (lane == 0) mbar_expect(BAR(B_S0 + sb), 2048);
        const uint32_t dst_a = mapa(SB + OFF_PBUF + (nt >> 1) * 512 + ((r + 4 * gg) * 4 + t) * 16, (nt & 1) * 2);
        const uint32_t dst_b = mapa(SB + OFF_PBUF + (nt >> 1) * 512 + ((r + 4 * gg) * 4 + t) * 16, (nt & 1) * 2 + 1);
        const uint32_t bar_a = mapa(BAR(B_P0), (nt & 1) * 2), bar_b = mapa(BAR(B_P0), (nt & 1) * 2 + 1);
        const uint32_t dst_m = mapa(SB + OFF_PBUF + 1024 + (r + 4 * gg + 8 * nt) * 4, t), bar_m = mapa(BAR(B_P0), t);
        const uint32_t sa = SB + OFF_SLOT + sb * 2048 + lane * 16;
        const uint32_t tok_prev = SB + OFF_WGT + 260 + (sb == 0 ? 2 : sb - 1) * 4, ref_prev = SB + OFF_REF + (sb == 0 ? 2 : sb - 1) * 16;
        asm volatile("barrier.cluster.wait.acquire.aligned;" ::: "memory");
        int sph = 0;
#pragma unroll 1
        for (int b = sb; b < nb; b += 3, sph ^= 1) {
            const uint32_t po = (b & 3) * PSTRIDE, bo = (b & 3) * 8;
            const bool valid = 2 * b + (nt >> 1) < nk;
            mbar_wait_cl(BAR(B_S0 + sb), sph);
            if (lane == 0 && b == 5) TRACE(16);
            const uint4 v0 = lds128(sa), v1 = lds128(sa + 512), v2 = lds128(sa + 1024), v3 = lds128(sa + 1536);
            float s0 = (__uint_as_float(v0.x) + __uint_as_float(v1.x)) + (__uint_as_float(v2.x) + __uint_as_float(v3.x));
            float s1 = (__uint_as_float(v0.y) + __uint_as_float(v1.y)) + (__uint_as_float(v2.y) + __uint_as_float(v3.y));
            float s2 = (__uint_as_float(v0.z) + __uint_as_float(v1.z)) + (__uint_as_float(v2.z) + __uint_as_float(v3.z));
            float s3 = (__uint_as_float(v0.w) + __uint_as_float(v1.w)) + (__uint_as_float(v2.w) + __uint_as_float(v3.w));
            const int i0 = valid ? f2o(fmaxf(s0, s1)) : INT_MIN, i1 = valid ? f2o(fmaxf(s2, s3)) : INT_MIN;
            int ra = __reduce_max_sync(~0u, gg ? INT_MIN : i0), rb = __reduce_max_sync(~0u, gg ? i0 : INT_MIN);
            int rc = __reduce_max_sync(~0u, gg ? INT_MIN : i1), rd = __reduce_max_sync(~0u, gg ? i1 : INT_MIN);
            if (b > 0) {
#pragma unroll 1
                for (int it = 0; it < SPIN_LIMIT; it++)
                    if ((int)lds32_acq(tok_prev) >= b) break;
                const uint4 pr = lds128(ref_prev);
                ra = max(ra, (int)pr.x); rb = max(rb, (int)pr.y); rc = max(rc, (int)pr.z); rd = max(rd, (int)pr.w);
            }
            __syncwarp();
            if (lane == 0) {
                sts128(SB + OFF_REF + sb * 16, make_uint4(ra, rb, rc, rd));
                sts32_rel(SB + OFF_WGT + 260 + sb * 4, b + 1);
            }
            const float n0 = o2f(gg ? rb : ra), n1 = o2f(gg ? rd : rc);
            const uint32_t w0 = pack2(ex2(s0 - n0), ex2(s1 - n0)), w1 = pack2(ex2(s2 - n1), ex2(s3 - n1));
            const uint32_t o0 = __shfl_xor_sync(~0u, w0, 8), o1 = __shfl_xor_sync(~0u, w1, 8);
            if (lane < 16) st_async_b32(dst_m + po, __float_as_uint(nt ? n1 : n0), bar_m + bo);
            if (valid) {
                const bool odd = nt & 1;
                const uint32_t x0 = odd ? o0 : w0, x1 = odd ? o1 : w1, x2 = odd ? w0 : o0, x3 = odd ? w1 : o1;
                st_async_v4(dst_a + po, x0, x1, x2, x3, bar_a + bo);
                st_async_v4(dst_b + po, x0, x1, x2, x3, bar_b + bo);
            }
            if (lane == 0 && b == 5) TRACE(17);
            if (lane == 0 && b + 3 < nb) mbar_expect(BAR(B_S0 + sb), (2 * (b + 3) + 1 < nk) ? 2048 : 1024);
        }
        if (sb == 2) {
            bar_sync(5, 288);
            combine_unit(SB, g_mb + (epoch & 1) * MB_SET + MB3 + (u0 + 8) * 1024, 8, nu > 8, 8 < (hA + 1) * 64 - u0, NC, lane);
            asm volatile("bar.arrive 3, 288;" ::: "memory");
            if (!full) return;
        }
        {
            const unsigned char* pm = g_mb + (epoch & 1) * MB_SET + MBM + ((sb == 0 ? hA : sb == 1 ? hB : h7) * NC_MAX + lane) * 8;
            uint2 a = make_uint2(0xff800000u, 0);
            if (lane < NC) {
#pragma unroll 1
                for (int it = 0; it < SPIN_LIMIT; it++) {
                    asm volatile("ld.relaxed.gpu.global.v2.u32 {%0,%1}, [%2];" : "=r"(a.x), "=r"(a.y) : "l"(pm) : "memory");
                    if (a.x != 0u) break;
                }
            }
            __syncwarp();
            const float mj = __uint_as_float(a.x);
            const float w = ex2(mj - o2f(__reduce_max_sync(~0u, f2o(mj))));
            if (sb < 2) {
                const int jj = lane & 15;
                const uint32_t d = SB + OFF_WGT + sb * 128 + ((lane >> 4) * 4 + ((jj & 7) >> 1)) * 16 + (jj >> 3) * 8 + (jj & 1) * 2;
                const __nv_bfloat16 hi = __float2bfloat16_rn(w), lo = __float2bfloat16_rn(w - __bfloat162float(hi));
                sts16(d, *reinterpret_cast<const uint16_t*>(&hi));
                sts16(d + 4, *reinterpret_cast<const uint16_t*>(&lo));
                asm volatile("bar.arrive 2, 352;" ::: "memory");
            } else {
                float L = w * __uint_as_float(a.y);
#pragma unroll
                for (int o = 16; o; o >>= 1) L += __shfl_xor_sync(~0u, L, o);
                if (lane == 0) sts32(SB + OFF_WGT + 256, __float_as_uint(__fdividef(1.f, L)));
                asm volatile("bar.arrive 4, 96;" ::: "memory");
            }
        }
        return;
    }

    if (tid == 0) {
#pragma unroll
        for (int i = 0; i < 4; i++) mbar_expect(BAR(B_P0 + i), 1088);
        mbar_expect(BAR(B_H), 896);
        mbar_expect(BAR(B_GU), 2048);
    }
    const uint32_t o1 = MB1 + cta * 1024 + warp * 128 + lane * 8;
    const uint32_t o3 = MB3 + ((g * 64 + r * 16 + warp * 2) * NC_MAX + j) * 32 + t * 8;
    const bool a4 = g < 4 || hB != hA;
    const uint32_t o4 = MB4 + ((g < 4 ? hA : hB) * 12 + ((tab.y >> (g < 4 ? 8 : 12)) & 15)) * 1024 + warp * 128 + (lane & 15) * 8;
    const uint32_t o5 = MB5 + h7 * 1792 + mb7 * 256 + warp * 32 + t * 8;
    const int li6 = (warp + 8 * g) * 4 + t;
    const bool a6 = g == 0 || (g == 1 && warp < 6);
    const uint32_t o6 = MB6 + ((r * 28 + (li6 >> 1)) * 28 + j) * 16 + (li6 & 1) * 8;
    const bool am = tid < 32 && (g & 3) == r && t < 2;
    const uint32_t om = MBM + ((g + 8 * t) * NC_MAX + j) * 8;
    const int ua = u0 + warp, ub = u0 + 8;
    const uint32_t o2a = MB2 + ((((ua & 63) >> 4) * 16 + (ua >> 6)) * 16 + (ua & 15)) * 32 + (lane >> 3) * 8;
    const uint32_t o2b = MB2 + ((((ub & 63) >> 4) * 16 + (ub >> 6)) * 16 + (ub & 15)) * 32 + (lane >> 3) * 8;
    if (full && lane < 16) mb_clear2(o1);
    if ((lane & 7) == 0) {
        mb_clear2(o2a);
        if (warp == 0 && nu > 8) mb_clear2(o2b);
    }
    unsigned char* const mb = g_mb + (epoch & 1) * MB_SET;

    if (full) {
        float v[14];
#pragma unroll
        for (int i = 0; i < 7; i++) { v[2 * i] = bflo(xr[i]); v[2 * i + 1] = bfhi(xr[i]); }
        float mean, den;
        ln_stats(v, mean, den);
        const float rden = __frcp_rn(den);
#pragma unroll
        for (int i = 0; i < 8; i++) xa[i] = pack2(ln_apply_r(bflo(xa[i]), mean, rden), ln_apply_r(bfhi(xa[i]), mean, rden));
        if (tid == 0) TRACE(14);
        float acc[4][4] = {};
        const int row = (lane & 7) + (lane & 8), ch = (warp & 1) * 4 + (lane >> 4);
        const uint32_t a0 = SB + OFF_CKV + 14 * UNIT + (warp >> 1) * 2048 + row * 128;
#pragma unroll
        for (int s = 0; s < 4; s++) {
            if ((s & 1) == 0) mbar_wait(BAR(s >> 1), 0);
            uint32_t b0, b1, b2, b3, b4, b5, b6, b7;
            ldsm4t(a0 + s * UNIT + ((ch ^ (row & 7)) << 4), b0, b1, b2, b3);
            ldsm4t(a0 + s * UNIT + (((ch + 2) ^ (row & 7)) << 4), b4, b5, b6, b7);
            mma16816(acc[0], xa[2 * s], 0, xa[2 * s + 1], 0, b0, b1);
            mma16816(acc[1], xa[2 * s], 0, xa[2 * s + 1], 0, b2, b3);
            mma16816(acc[2], xa[2 * s], 0, xa[2 * s + 1], 0, b4, b5);
            mma16816(acc[3], xa[2 * s], 0, xa[2 * s + 1], 0, b6, b7);
        }
        const float v0 = (g & 2) ? ((g & 1) ? acc[3][0] : acc[2][0]) : ((g & 1) ? acc[1][0] : acc[0][0]);
        const float v1 = (g & 2) ? ((g & 1) ? acc[3][1] : acc[2][1]) : ((g & 1) ? acc[1][1] : acc[0][1]);
        if (lane < 16) mb_put2f(mb + o1, v0, v1);
        __syncwarp();
        if (lane == 0) mbar_arrive(BAR(G_P1));
    }
    if (tid == 0) TRACE(1);
    mb_clear2(o3); mb_clear2(o3 + 1024); mb_clear2(o3 + 524288); mb_clear2(o3 + 524288 + 1024);
    if (a4) mb_clear2(o4);
    if (am) mb_clear2(om);
    if (full) {
        if (lane < 4) mb_clear2(o5);
        if (a6) mb_clear2(o6);
    }
    if (tid < 64 || (tid < 128 && hB != hA)) {
        const int i = tid & 63, hs = tid >> 6;
        uint4 v[7];
        mb_poll<7, 1024>(mb + MB1 + (hs ? hB : hA) * 7168 + i * 16, 7, v);
        float a0 = 0.f, a1 = 0.f, a2 = 0.f, a3 = 0.f;
#pragma unroll
        for (int k = 0; k < 7; k++) {
            a0 += __uint_as_float(v[k].x); a1 += __uint_as_float(v[k].y);
            a2 += __uint_as_float(v[k].z); a3 += __uint_as_float(v[k].w);
        }
        const uint32_t d = SB + OFF_QST + hs * 512 + frag_off(2 * i);
        sts32(d, pack2(a0, a1));
        sts32(d + 16, pack2(a2, a3));
    }
    bar_sync(1, 256);
    if (tid == 0) TRACE(2);
    {
        const int row = (lane & 7) + (lane & 8), cs = lane >> 4;
        const float sc = 0.0625f * 1.4426950408889634f;
        {
            const uint32_t qs = SB + OFF_QST + ((ua >> 6) != hA ? 512 : 0) + t * 16;
            uint4 q[8];
#pragma unroll
            for (int s2 = 0; s2 < 8; s2++) q[s2] = lds128(qs + s2 * 64);
            mbar_wait(BAR(g_uk + (warp >> 1)), 0);
            float c[4][4] = {};
            const uint32_t a0 = SB + OFF_WA + warp * UNIT + row * 128;
#pragma unroll
            for (int s2 = 0; s2 < 8; s2++) {
                uint32_t r0, r1, r2, r3, r4, r5, r6, r7;
                ldsm4(a0 + (s2 >> 1) * 2048 + ((((s2 & 1) * 4 + cs) ^ (row & 7)) << 4), r0, r1, r2, r3);
                ldsm4(a0 + (s2 >> 1) * 2048 + ((((s2 & 1) * 4 + 2 + cs) ^ (row & 7)) << 4), r4, r5, r6, r7);
                mma16816(c[(s2 & 1) * 2], r0, r1, r2, r3, q[s2].x, q[s2].y);
                mma16816(c[(s2 & 1) * 2 + 1], r4, r5, r6, r7, q[s2].z, q[s2].w);
            }
            const float lo = ((c[0][0] + c[1][0]) + (c[2][0] + c[3][0])) * sc, hi = ((c[0][2] + c[1][2]) + (c[2][2] + c[3][2])) * sc;
            const float lo2 = __shfl_down_sync(~0u, lo, 4), hi2 = __shfl_down_sync(~0u, hi, 4);
            if ((lane & 7) == 0) mb_put2(mb + o2a, pack2(lo, lo2), pack2(hi, hi2));
        }
        if (nu > 8 && warp == 0) {
            const uint32_t qs = SB + OFF_QST + ((ub >> 6) != hA ? 512 : 0) + t * 16;
            uint4 q[8];
#pragma unroll
            for (int s2 = 0; s2 < 8; s2++) q[s2] = lds128(qs + s2 * 64);
            mbar_wait(BAR(g_uk + 4), 0);
            float c[4][4] = {};
            const uint32_t a0 = SB + OFF_WA + 8 * UNIT + row * 128;
#pragma unroll
            for (int s2 = 0; s2 < 8; s2++) {
                uint32_t r0, r1, r2, r3, r4, r5, r6, r7;
                ldsm4(a0 + (s2 >> 1) * 2048 + ((((s2 & 1) * 4 + cs) ^ (row & 7)) << 4), r0, r1, r2, r3);
                ldsm4(a0 + (s2 >> 1) * 2048 + ((((s2 & 1) * 4 + 2 + cs) ^ (row & 7)) << 4), r4, r5, r6, r7);
                mma16816(c[(s2 & 1) * 2], r0, r1, r2, r3, q[s2].x, q[s2].y);
                mma16816(c[(s2 & 1) * 2 + 1], r4, r5, r6, r7, q[s2].z, q[s2].w);
            }
            const float lo = ((c[0][0] + c[1][0]) + (c[2][0] + c[3][0])) * sc, hi = ((c[0][2] + c[1][2]) + (c[2][2] + c[3][2])) * sc;
            const float lo2 = __shfl_down_sync(~0u, lo, 4), hi2 = __shfl_down_sync(~0u, hi, 4);
            if ((lane & 7) == 0) mb_put2(mb + o2b, pack2(lo, lo2), pack2(hi, hi2));
        }
    }
    if (tid == 0) TRACE(3);
    {
        uint4 v[2];
        mb_poll<2, 4096>(mb + MB2 + r * 8192 + tid * 16, 2, v);
        bar_sync(1, 256);
        const uint32_t a = SB + OFF_WA + ((tid >> 1) & 15) * 512 + ((tid >> 5) * 4 + (tid & 1) * 2) * 16;
        sts128(a, make_uint4(v[0].x, v[1].x, v[0].y, v[1].y));
        sts128(a + 16, make_uint4(v[0].z, v[1].z, v[0].w, v[1].w));
        asm volatile("bar.arrive 6, 384;" ::: "memory");
    }
    asm volatile("barrier.cluster.wait.acquire.aligned;" ::: "memory");
    if (tid == 0) TRACE(4);
    {
        float acc[4][4] = {};
        float mr0 = -INFINITY, mr1 = -INFINITY, tl[4] = {};
        const int prow = (lane & 7) + (lane & 8), pch = (warp & 1) * 4 + (lane >> 4);
        const uint32_t p_src0 = SB + OFF_CKV + (warp >> 1) * 2048 + prow * 128 + ((pch ^ (prow & 7)) << 4);
        const uint32_t p_src1 = SB + OFF_CKV + (warp >> 1) * 2048 + prow * 128 + (((pch + 2) ^ (prow & 7)) << 4);
        const uint32_t one = 0x3f803f80u;
#pragma unroll 1
        for (int b = 0; b < nb; b++) {
            const int pb = b & 3;
            const bool two = 2 * b + 1 < nk;
            const uint32_t pbase = SB + OFF_PBUF + pb * PSTRIDE;
            mbar_wait_cl(BAR(B_P0 + pb), (b >> 2) & 1);
            if (tid == 0) TRACE(21 + b);
            uint32_t b0[8], b1[8];
            const float mb0 = __uint_as_float(lds32(pbase + 1024 + g * 4));
            const float mb1 = __uint_as_float(lds32(pbase + 1024 + 32 + g * 4));
            const uint4 p0 = lds128(pbase + lane * 16);
            ldsm4t(p_src0 + 2 * b * UNIT, b0[0], b0[1], b0[2], b0[3]);
            ldsm4t(p_src1 + 2 * b * UNIT, b0[4], b0[5], b0[6], b0[7]);
            uint4 p1;
            if (two) {
                p1 = lds128(pbase + 512 + lane * 16);
                ldsm4t(p_src0 + (2 * b + 1) * UNIT, b1[0], b1[1], b1[2], b1[3]);
                ldsm4t(p_src1 + (2 * b + 1) * UNIT, b1[4], b1[5], b1[6], b1[7]);
            }
            if (__any_sync(~0u, mb0 != mr0 || mb1 != mr1)) {
                const float al0 = ex2(mr0 - mb0), al1 = ex2(mr1 - mb1);
                mr0 = mb0; mr1 = mb1;
#pragma unroll
                for (int i = 0; i < 4; i++) { acc[i][0] *= al0; acc[i][1] *= al0; acc[i][2] *= al1; acc[i][3] *= al1; }
                tl[0] *= al0; tl[2] *= al1;
            }
#pragma unroll
            for (int i = 0; i < 4; i++) mma16816(acc[i], p0.x, p0.y, p0.z, p0.w, b0[2 * i], b0[2 * i + 1]);
            mma16816(tl, p0.x, p0.y, p0.z, p0.w, one, one);
            if (two) {
#pragma unroll
                for (int i = 0; i < 4; i++) mma16816(acc[i], p1.x, p1.y, p1.z, p1.w, b1[2 * i], b1[2 * i + 1]);
                mma16816(tl, p1.x, p1.y, p1.z, p1.w, one, one);
            }
            if (tid == 0 && b + 4 < nb) mbar_expect(BAR(B_P0 + pb), (2 * (b + 4) + 1 < nk) ? 1088 : 576);
            __syncwarp();
            if (lane == 0) red_add_rel(SB + OFF_PVC + pb * 4, 1);
        }
        if (am) mb_put2f(mb + om, t ? mr1 : mr0, t ? tl[2] : tl[0]);
        mb_put2(mb + o3, pack2(acc[0][0], acc[0][1]), pack2(acc[1][0], acc[1][1]));
        mb_put2(mb + o3 + 1024, pack2(acc[2][0], acc[2][1]), pack2(acc[3][0], acc[3][1]));
        mb_put2(mb + o3 + 524288, pack2(acc[0][2], acc[0][3]), pack2(acc[1][2], acc[1][3]));
        mb_put2(mb + o3 + 524288 + 1024, pack2(acc[2][2], acc[2][3]), pack2(acc[3][2], acc[3][3]));
    }
    if (tid == 0) TRACE(5);
    {
        bar_sync(5, 288);
        uint32_t wb[9][8];
        const int p = (lane & 7) + (lane & 8);
        const int prow = ((p >> 1) & 1) * 8 + (p >> 2) * 2 + (p & 1), pch = (warp & 1) * 4 + (lane >> 4);
        const uint32_t src0 = SB + OFF_WA + (warp >> 1) * 2048 + prow * 128 + ((pch ^ (prow & 7)) << 4);
        const uint32_t src1 = SB + OFF_WA + (warp >> 1) * 2048 + prow * 128 + (((pch + 2) ^ (prow & 7)) << 4);
#pragma unroll
        for (int ul = 0; ul < 9; ul++) {
            const uint32_t uo = (ul < 8 || nu > 8) ? ul * UNIT : 0;
            if ((ul & 1) == 0 && (ul < 8 || nu > 8)) mbar_wait(BAR(g_uv + (ul >> 1)), 0);
            ldsm4t(src0 + uo, wb[ul][0], wb[ul][1], wb[ul][2], wb[ul][3]);
            ldsm4t(src1 + uo, wb[ul][4], wb[ul][5], wb[ul][6], wb[ul][7]);
        }
        if (tid == 0) TRACE(18);
        const int nA = (hA + 1) * 64 - u0;
        combine_unit(SB, mb + MB3 + ua * 1024, warp, true, warp < nA, NC, lane);
        bar_sync(3, 288);
        if (tid == 0) TRACE(6);
        float acc[2][4][4] = {};
#pragma unroll
        for (int ul = 0; ul < 9; ul++) {
            uint4 a = lds128(SB + OFF_AFR + ul * 64 + t * 16);
            if ((ul < nA) != (g < 4)) a = make_uint4(0, 0, 0, 0);
#pragma unroll
            for (int i = 0; i < 4; i++) mma16816(acc[ul & 1][i], a.x, a.y, a.z, a.w, wb[ul][2 * i], wb[ul][2 * i + 1]);
        }
        float v0, v1;
        {
            const int i = g & 3;
            float e[4][2];
#pragma unroll
            for (int k = 0; k < 4; k++) {
                e[k][0] = (acc[0][k][0] + acc[0][k][2]) + (acc[1][k][0] + acc[1][k][2]);
                e[k][1] = (acc[0][k][1] + acc[0][k][3]) + (acc[1][k][1] + acc[1][k][3]);
            }
            v0 = (i & 2) ? ((i & 1) ? e[3][0] : e[2][0]) : ((i & 1) ? e[1][0] : e[0][0]);
            v1 = (i & 2) ? ((i & 1) ? e[3][1] : e[2][1]) : ((i & 1) ? e[1][1] : e[0][1]);
        }
        if (a4) mb_put2f(mb + o4, v0, v1);
    }
    if (tid == 0) TRACE(7);
    if (!full) return;

    {
        if (tid < 64) {
            uint4 v[10];
            mb_poll<10, 1024>(mb + MB4 + h7 * 12288 + tid * 16, (tab.y >> 16) & 15, v);
            float a0 = 0.f, a1 = 0.f, a2 = 0.f, a3 = 0.f;
#pragma unroll
            for (int k = 0; k < 10; k++) {
                a0 += __uint_as_float(v[k].x); a1 += __uint_as_float(v[k].y);
                a2 += __uint_as_float(v[k].z); a3 += __uint_as_float(v[k].w);
            }
            bar_sync(4, 96);
            const float rl = __uint_as_float(lds32(SB + OFF_WGT + 256));
            const uint32_t d = SB + OFF_CTX + frag_off(2 * tid);
            sts32(d, pack2(a0 * rl, a1 * rl));
            sts32(d + 16, pack2(a2 * rl, a3 * rl));
        }
        mbar_wait(BAR(g_wo), 0);
        mbar_wait(BAR(g_wo + 1), 0);
        uint32_t b[8][4];
        const uint32_t src = SB + OFF_CKV + lane * 128 + ((warp ^ (lane & 7)) << 4);
#pragma unroll
        for (int s2 = 0; s2 < 8; s2++) ldsm4t(src + s2 * 4096, b[s2][0], b[s2][1], b[s2][2], b[s2][3]);
        bar_sync(1, 256);
        if (tid == 0) TRACE(8);
        float c[4][4] = {};
#pragma unroll
        for (int s2 = 0; s2 < 8; s2++) {
            const uint4 a = lds128(SB + OFF_CTX + s2 * 64 + t * 16);
            mma16816(c[(s2 & 1) * 2], a.x, 0, a.y, 0, b[s2][0], b[s2][1]);
            mma16816(c[(s2 & 1) * 2 + 1], a.z, 0, a.w, 0, b[s2][2], b[s2][3]);
        }
        if (lane < 4) mb_put2f(mb + o5, (c[0][0] + c[1][0]) + (c[2][0] + c[3][0]), (c[0][1] + c[1][1]) + (c[2][1] + c[3][1]));
    }
    if (tid == 0) TRACE(9);

    if (warp == 0 && lane < 28) {
        const int w = (r & 1) * 56 + 2 * lane;
        const uint32_t d0 = SB + OFF_H + (r >> 1) * 448 + frag_off(w);
        uint32_t da[4], ba[4];
#pragma unroll
        for (int k = 0; k < 4; k++) { da[k] = mapa(d0, k); ba[k] = mapa(BAR(B_H), k); }
        uint4 v[16];
        mb_poll<16, 1792>(mb + MB5 + r * 448 + lane * 16, 16, v);
        float a0 = 0.f, a1 = 0.f, a2 = 0.f, a3 = 0.f, e0 = 0.f, e1 = 0.f, e2 = 0.f, e3 = 0.f;
#pragma unroll
        for (int k = 0; k < 8; k++) {
            a0 += __uint_as_float(v[k].x); a1 += __uint_as_float(v[k].y);
            a2 += __uint_as_float(v[k].z); a3 += __uint_as_float(v[k].w);
            e0 += __uint_as_float(v[8 + k].x); e1 += __uint_as_float(v[8 + k].y);
            e2 += __uint_as_float(v[8 + k].z); e3 += __uint_as_float(v[8 + k].w);
        }
        const uint32_t h0 = pack2(bflo(xw0) + bf16r(a0 + e0), bfhi(xw0) + bf16r(a1 + e1));
        const uint32_t h1 = pack2(bflo(xw1) + bf16r(a2 + e2), bfhi(xw1) + bf16r(a3 + e3));
#pragma unroll
        for (int k = 0; k < 4; k++) {
            st_async_b32(da[k], h0, ba[k]);
            st_async_b32(da[k] + 16, h1, ba[k]);
        }
    }
    __syncwarp();
    float mean, den;
    {
        mbar_wait(BAR(g_gu), 0);
        mbar_wait(BAR(g_gu + 1), 0);
        uint32_t b[7][4];
        const uint32_t src = SB + OFF_CKV + 4 * UNIT + lane * 128 + ((warp ^ (lane & 7)) << 4);
#pragma unroll
        for (int s2 = 0; s2 < 7; s2++) ldsm4t(src + s2 * 4096, b[s2][0], b[s2][1], b[s2][2], b[s2][3]);
        const uint32_t gdst = mapa(SB + OFF_GU + r * 512 + (warp * 4 + t) * 16, g & 3), gbar = mapa(BAR(B_GU), g & 3);
        mbar_wait_cl(BAR(B_H), 0);
        if (tid == 0) TRACE(10);
        float c[4][4] = {};
        const uint32_t one = 0x3f803f80u;
#pragma unroll
        for (int s2 = 0; s2 < 7; s2++) {
            const uint4 a = lds128(SB + OFF_H + (r >> 1) * 448 + s2 * 64 + t * 16);
            mma16816(c[(s2 & 1) * 2], a.x, one, a.y, one, b[s2][0], b[s2][1]);
            mma16816(c[(s2 & 1) * 2 + 1], a.z, one, a.w, one, b[s2][2], b[s2][3]);
        }
        if (g < 4)
            st_async_v4(gdst, __float_as_uint((c[0][0] + c[1][0]) + (c[2][0] + c[3][0])),
                        __float_as_uint((c[0][1] + c[1][1]) + (c[2][1] + c[3][1])), __float_as_uint((c[0][2] + c[1][2]) + (c[2][2] + c[3][2])),
                        __float_as_uint((c[0][3] + c[1][3]) + (c[2][3] + c[3][3])), gbar);
        float v[14];
#pragma unroll
        for (int i = 0; i < 7; i++) {
            const uint32_t w = lds32(SB + OFF_H + (lane + 32 * i) * 4);
            v[2 * i] = bflo(w); v[2 * i + 1] = bfhi(w);
        }
        ln_stats(v, mean, den);
    }
    {
        mbar_wait(BAR(g_wd), 0);
        uint32_t b[4][4];
        const uint32_t src = SB + OFF_CKV + 8 * UNIT + lane * 128 + ((warp ^ (lane & 7)) << 4);
        ldsm4t(src, b[0][0], b[0][1], b[0][2], b[0][3]);
        ldsm4t(src + 4096, b[1][0], b[1][1], b[1][2], b[1][3]);
        ldsm4t(src + UNIT, b[2][0], b[2][1], b[2][2], b[2][3]);
        ldsm4t(src + UNIT + 4096, b[3][0], b[3][1], b[3][2], b[3][3]);
        const float inv = __fdividef(1.f, den);
        mbar_wait_cl(BAR(B_GU), 0);
        if (tid == 0) TRACE(11);
        const uint32_t ga = SB + OFF_GU + (((g & 3) * 2 + (g >> 2)) * 4 + t) * 16;
        const uint4 p0 = lds128(ga), p1 = lds128(ga + 512), p2 = lds128(ga + 1024), p3 = lds128(ga + 1536);
        const float g0 = bf16r(((__uint_as_float(p0.x) + __uint_as_float(p2.x)) - mean * (__uint_as_float(p0.z) + __uint_as_float(p2.z))) * inv);
        const float g1 = bf16r(((__uint_as_float(p0.y) + __uint_as_float(p2.y)) - mean * (__uint_as_float(p0.w) + __uint_as_float(p2.w))) * inv);
        const float u0v = bf16r(((__uint_as_float(p1.x) + __uint_as_float(p3.x)) - mean * (__uint_as_float(p1.z) + __uint_as_float(p3.z))) * inv);
        const float u1v = bf16r(((__uint_as_float(p1.y) + __uint_as_float(p3.y)) - mean * (__uint_as_float(p1.w) + __uint_as_float(p3.w))) * inv);
        const float s0 = bf16r(__fdividef(1.f, 1.f + __expf(-g0))), s1 = bf16r(__fdividef(1.f, 1.f + __expf(-g1)));
        const uint32_t hw = pack2(s0 * u0v, s1 * u1v);
        uint32_t a[8];
#pragma unroll
        for (int k = 0; k < 8; k++) a[k] = __shfl_sync(~0u, hw, k * 4 + t);
        float c0[4] = {}, c1[4] = {}, c2[4] = {}, c3[4] = {};
        mma16816(c0, a[0], 0, a[4], 0, b[0][0], b[0][1]);
        mma16816(c1, a[0], 0, a[4], 0, b[2][0], b[2][1]);
        mma16816(c2, a[1], 0, a[5], 0, b[0][2], b[0][3]);
        mma16816(c3, a[1], 0, a[5], 0, b[2][2], b[2][3]);
        mma16816(c0, a[2], 0, a[6], 0, b[1][0], b[1][1]);
        mma16816(c1, a[2], 0, a[6], 0, b[3][0], b[3][1]);
        mma16816(c2, a[3], 0, a[7], 0, b[1][2], b[1][3]);
        mma16816(c3, a[3], 0, a[7], 0, b[3][2], b[3][3]);
        if (a6) mb_put2f(mb + o6, g ? c1[0] + c3[0] : c0[0] + c2[0], g ? c1[1] + c3[1] : c0[1] + c2[1]);
    }
    if (tid == 0) TRACE(12);
    if (warp != 0) return;
    {
        const int k = (lane >> 1) & 3;
        const uint32_t hw = lds32(SB + OFF_H + (r >> 1) * 448 + frag_off((r & 1) * 56 + j * 2 + (k >> 1)));
        uint4 v[4];
        const int n = lane < 4 ? 4 : lane < 8 ? 3 : 0;
        mb_poll<4, 128>(mb + MB6 + ((r * 28 + j) * 28 + lane) * 16, n, v);
        float v0 = (__uint_as_float(v[0].x) + __uint_as_float(v[1].x)) + (__uint_as_float(v[2].x) + __uint_as_float(v[3].x));
        float v1 = (__uint_as_float(v[0].y) + __uint_as_float(v[1].y)) + (__uint_as_float(v[2].y) + __uint_as_float(v[3].y));
        float v2 = (__uint_as_float(v[0].z) + __uint_as_float(v[1].z)) + (__uint_as_float(v[2].z) + __uint_as_float(v[3].z));
        float v3 = (__uint_as_float(v[0].w) + __uint_as_float(v[1].w)) + (__uint_as_float(v[2].w) + __uint_as_float(v[3].w));
        __syncwarp();
        const bool up = lane & 4;
        const float s0 = up ? v0 : v2, s1 = up ? v1 : v3;
        const float k0v = up ? v2 : v0, k1v = up ? v3 : v1;
        v0 = k0v + __shfl_xor_sync(~0u, s0, 4);
        v1 = k1v + __shfl_xor_sync(~0u, s1, 4);
        const bool up2 = lane & 2;
        const float s2 = up2 ? v0 : v1, k2v = up2 ? v1 : v0;
        v0 = k2v + __shfl_xor_sync(~0u, s2, 2);
        v0 += __shfl_xor_sync(~0u, v0, 1);
        if (lane < 8 && (lane & 1) == 0)
            P.out[r * 112 + j * 4 + k] = __float2bfloat16_rn(((k & 1) ? bfhi(hw) : bflo(hw)) + bf16r(v0));
        if (cta == 0 && lane == 0) g_epoch = epoch + 1;
        if (tid == 0) TRACE(13);
    }
}

__device__ float f_q[4096], f_qa[16 * 1024], f_s[16 * 8192], f_cc[64 * 16 * 1024], f_ctx[4096], f_h[448], f_hh[1792];

__device__ __forceinline__ void block_ln(const float* v  , float* o  ) {
    float a[14];
    const int lane = threadIdx.x & 31;
#pragma unroll
    for (int i = 0; i < 14; i++) a[i] = v[lane + 32 * i];
    float mb, den;
    ln_stats(a, mb, den);
    for (int i = threadIdx.x; i < 448; i += blockDim.x) o[i] = bf16r(ln_apply(v[i], mb, den));
    __syncthreads();
}
__global__ void fb_q(const __nv_bfloat16* x, const __nv_bfloat16* wq) {
    __shared__ float xs[448], xn[448];
    for (int i = threadIdx.x; i < 448; i += blockDim.x) xs[i] = __bfloat162float(x[i]);
    __syncthreads();
    block_ln(xs, xn);
    const int c = blockIdx.x * blockDim.x + threadIdx.x;
    float a = 0.f;
    for (int m = 0; m < 448; m++) a += xn[m] * __bfloat162float(wq[(size_t)m * 4096 + c]);
    f_q[c] = bf16r(a);
}
__global__ void fb_qabs(const __nv_bfloat16* wuk) {
    const int row = blockIdx.x * 8 + (threadIdx.x >> 5), lane = threadIdx.x & 31;
    const int h = row & 15, c = row >> 4;
    float a = 0.f;
    for (int d = lane; d < 256; d += 32) a += f_q[h * 256 + d] * __bfloat162float(wuk[(size_t)row * 256 + d]);
    for (int o = 16; o; o >>= 1) a += __shfl_xor_sync(~0u, a, o);
    if (lane == 0) f_qa[h * 1024 + c] = a * 0.0625f;
}
__global__ void fb_scores(const __nv_bfloat16* ckv) {
    const int k = blockIdx.x * 8 + (threadIdx.x >> 5), lane = threadIdx.x & 31;
    float a[16] = {};
    for (int c = lane; c < 1024; c += 32) {
        const float v = __bfloat162float(ckv[(size_t)k * 1024 + c]);
#pragma unroll
        for (int h = 0; h < 16; h++) a[h] += v * f_qa[h * 1024 + c];
    }
#pragma unroll
    for (int h = 0; h < 16; h++) {
        for (int o = 16; o; o >>= 1) a[h] += __shfl_xor_sync(~0u, a[h], o);
        if (lane == 0) f_s[h * 8192 + k] = a[h];
    }
}
__global__ void fb_softmax() {
    __shared__ float red[32];
    float* s = f_s + blockIdx.x * 8192;
    float m = -INFINITY;
    for (int i = threadIdx.x; i < 8192; i += blockDim.x) m = fmaxf(m, s[i]);
    for (int o = 16; o; o >>= 1) m = fmaxf(m, __shfl_xor_sync(~0u, m, o));
    if ((threadIdx.x & 31) == 0) red[threadIdx.x >> 5] = m;
    __syncthreads();
    m = red[0];
    for (int i = 1; i < (int)(blockDim.x >> 5); i++) m = fmaxf(m, red[i]);
    __syncthreads();
    float l = 0.f;
    for (int i = threadIdx.x; i < 8192; i += blockDim.x) { const float e = __expf(s[i] - m); s[i] = e; l += e; }
    for (int o = 16; o; o >>= 1) l += __shfl_xor_sync(~0u, l, o);
    if ((threadIdx.x & 31) == 0) red[threadIdx.x >> 5] = l;
    __syncthreads();
    l = 0.f;
    for (int i = 0; i < (int)(blockDim.x >> 5); i++) l += red[i];
    const float inv = 1.f / l;
    for (int i = threadIdx.x; i < 8192; i += blockDim.x) s[i] *= inv;
}
__global__ void fb_pv(const __nv_bfloat16* ckv) {
    const int c = blockIdx.y * 256 + threadIdx.x, kb = blockIdx.x * 128;
    float a[16] = {};
    for (int k = kb; k < kb + 128; k++) {
        const float v = __bfloat162float(ckv[(size_t)k * 1024 + c]);
#pragma unroll
        for (int h = 0; h < 16; h++) a[h] += v * f_s[h * 8192 + k];
    }
#pragma unroll
    for (int h = 0; h < 16; h++) f_cc[(blockIdx.x * 16 + h) * 1024 + c] = a[h];
}
__global__ void fb_ctx(const __nv_bfloat16* wuv) {
    __shared__ float cc[1024];
    const int h = blockIdx.x;
    for (int c = threadIdx.x; c < 1024; c += 256) {
        float a = 0.f;
        for (int i = 0; i < 64; i++) a += f_cc[(i * 16 + h) * 1024 + c];
        cc[c] = a;
    }
    __syncthreads();
    float a = 0.f;
    for (int c = 0; c < 1024; c++) a += cc[c] * __bfloat162float(wuv[(size_t)c * 4096 + h * 256 + threadIdx.x]);
    f_ctx[h * 256 + threadIdx.x] = bf16r(a);
}
__global__ void fb_o(const __nv_bfloat16* x, const __nv_bfloat16* wo) {
    __shared__ float red[8][32];
    const int m = blockIdx.x * 32 + (threadIdx.x & 31), p = threadIdx.x >> 5;
    float a = 0.f;
    for (int i = p * 512; i < p * 512 + 512; i++) a += f_ctx[i] * __bfloat162float(wo[(size_t)i * 448 + m]);
    red[p][threadIdx.x & 31] = a;
    __syncthreads();
    if (p == 0) {
        for (int i = 1; i < 8; i++) a += red[i][threadIdx.x];
        f_h[m] = bf16r(__bfloat162float(x[m]) + bf16r(a));
    }
}
__global__ void fb_gu(const __nv_bfloat16* wg, const __nv_bfloat16* wu) {
    __shared__ float hs[448], hn[448];
    for (int i = threadIdx.x; i < 448; i += blockDim.x) hs[i] = f_h[i];
    __syncthreads();
    block_ln(hs, hn);
    const int f = blockIdx.x * 64 + threadIdx.x;
    float a = 0.f, b = 0.f;
    for (int m = 0; m < 448; m++) {
        a += hn[m] * __bfloat162float(wg[(size_t)m * 1792 + f]);
        b += hn[m] * __bfloat162float(wu[(size_t)m * 1792 + f]);
    }
    f_hh[f] = bf16r(bf16r(1.f / (1.f + __expf(-bf16r(a)))) * bf16r(b));
}
__global__ void fb_down(const __nv_bfloat16* wd, __nv_bfloat16* out) {
    __shared__ float red[8][32];
    const int m = blockIdx.x * 32 + (threadIdx.x & 31), p = threadIdx.x >> 5;
    float a = 0.f;
    for (int i = p * 224; i < p * 224 + 224; i++) a += f_hh[i] * __bfloat162float(wd[(size_t)i * 448 + m]);
    red[p][threadIdx.x & 31] = a;
    __syncthreads();
    if (p == 0) {
        for (int i = 1; i < 8; i++) a += red[i][threadIdx.x];
        out[m] = __float2bfloat16_rn(f_h[m] + bf16r(a));
    }
}

typedef CUresult (*EncodeFn)(CUtensorMap*, CUtensorMapDataType, cuuint32_t, void*, const cuuint64_t*, const cuuint64_t*,
                             const cuuint32_t*, const cuuint32_t*, CUtensorMapInterleave, CUtensorMapSwizzle,
                             CUtensorMapL2promotion, CUtensorMapFloatOOBfill);

bool encode3(EncodeFn enc, CUtensorMap* m, const void* p, uint64_t rows, uint64_t rowbytes) {
    cuuint64_t dim[3] = {64, rows, rowbytes / 128};
    cuuint64_t str[2] = {rowbytes, 128};
    cuuint32_t box[3] = {64, 16, 4}, es[3] = {1, 1, 1};
    return enc(m, CU_TENSOR_MAP_DATA_TYPE_BFLOAT16, 3, const_cast<void*>(p), dim, str, box, es, CU_TENSOR_MAP_INTERLEAVE_NONE,
               CU_TENSOR_MAP_SWIZZLE_128B, CU_TENSOR_MAP_L2_PROMOTION_NONE, CU_TENSOR_MAP_FLOAT_OOB_FILL_NONE) == CUDA_SUCCESS;
}
bool encode2(EncodeFn enc, CUtensorMap* m, const void* p, uint64_t rows, uint64_t cols, uint32_t boxrows) {
    cuuint64_t dim[2] = {cols, rows};
    cuuint64_t str[1] = {cols * 2};
    cuuint32_t box[2] = {64, boxrows}, es[2] = {1, 1};
    return enc(m, CU_TENSOR_MAP_DATA_TYPE_BFLOAT16, 2, const_cast<void*>(p), dim, str, box, es, CU_TENSOR_MAP_INTERLEAVE_NONE,
               CU_TENSOR_MAP_SWIZZLE_128B, CU_TENSOR_MAP_L2_PROMOTION_NONE, CU_TENSOR_MAP_FLOAT_OOB_FILL_NONE) == CUDA_SUCCESS;
}

int g_force_fallback = 0;
int g_window = 0x333;

}

extern "C" void kernel_launch(void* const* d_in, const int* in_sizes, int n_in, void* d_out, int out_size) {
    const __nv_bfloat16* x = (const __nv_bfloat16*)d_in[0];
    const __nv_bfloat16* ckv = (const __nv_bfloat16*)d_in[1];
    const __nv_bfloat16* wq = (const __nv_bfloat16*)d_in[2];
    const __nv_bfloat16* wuk = (const __nv_bfloat16*)d_in[3];
    const __nv_bfloat16* wuv = (const __nv_bfloat16*)d_in[4];
    const __nv_bfloat16* wo = (const __nv_bfloat16*)d_in[5];
    const __nv_bfloat16* wg = (const __nv_bfloat16*)d_in[7];
    const __nv_bfloat16* wu = (const __nv_bfloat16*)d_in[8];
    const __nv_bfloat16* wd = (const __nv_bfloat16*)d_in[9];
    __nv_bfloat16* out = (__nv_bfloat16*)d_out;
    cudaStream_t st = cudaStreamPerThread;

    static int s_init = 0, s_nc = 0;
    static EncodeFn s_enc = nullptr;
    cudaLaunchConfig_t cfg = {};
    cudaLaunchAttribute at[1];
    at[0].id = cudaLaunchAttributeClusterDimension;
    at[0].val.clusterDim.x = 4; at[0].val.clusterDim.y = 1; at[0].val.clusterDim.z = 1;
    cfg.blockDim = dim3(NTHR); cfg.dynamicSmemBytes = SMEM_BYTES + 128; cfg.stream = st; cfg.attrs = at; cfg.numAttrs = 1;
    if (!s_init) {
        s_init = 1;
        void* fn = nullptr;
        cudaDriverEntryPointQueryResult qr;
        if (cudaGetDriverEntryPoint("cuTensorMapEncodeTiled", &fn, cudaEnableDefault, &qr) == cudaSuccess &&
            qr == cudaDriverEntryPointSuccess)
            s_enc = (EncodeFn)fn;
        int nc = 0;
        cfg.gridDim = dim3(4 * NC_MAX);
        if (cudaFuncSetAttribute(fused_kernel, cudaFuncAttributeMaxDynamicSharedMemorySize, SMEM_BYTES + 128) == cudaSuccess &&
            cudaOccupancyMaxActiveClusters(&nc, fused_kernel, &cfg) == cudaSuccess)
            s_nc = nc > NC_MAX ? NC_MAX : nc;
        (void)cudaGetLastError();
    }
    Params P;
    bool ok = s_enc != nullptr && s_nc >= NC_MIN && !g_force_fallback;
    ok = ok && encode3(s_enc, &P.wq, wq, 448, 8192) && encode3(s_enc, &P.wuk, wuk, 1024, 8192) &&
         encode3(s_enc, &P.ckv, ckv, 8192, 2048) && encode3(s_enc, &P.wuv, wuv, 1024, 8192) &&
         encode2(s_enc, &P.wo, wo, 4096, 448, 64) && encode2(s_enc, &P.wg, wg, 448, 1792, 112) &&
         encode2(s_enc, &P.wu, wu, 448, 1792, 112) && encode2(s_enc, &P.wd, wd, 1792, 448, 64);
    if (ok) {
        P.x = x; P.out = out; P.NC = s_nc; P.W = g_window;
        const int N = 4 * s_nc;
        int ustart[4 * NC_MAX + 1], kstart[NC_MAX + 1];
        {
            const int kbase = 512 / s_nc, kext = 512 - kbase * s_nc;
            kstart[0] = 0;
            for (int jj = 0; jj < s_nc; jj++) kstart[jj + 1] = kstart[jj] + kbase + (jj >= s_nc - kext ? 1 : 0);
            const int ubase = 1024 / N;
            int uext = 1024 - ubase * N;
            const int light = N - 112, lext = uext < light ? uext : light;
            uext -= lext;
            ustart[0] = 0;
            for (int c = 0; c < N; c++) {
                const int extra = c < 112 ? ((c + 1) * uext / 112 - c * uext / 112) : (c - 112 < lext ? 1 : 0);
                ustart[c + 1] = ustart[c] + ubase + extra;
            }
        }
        auto owner = [&](int u) { int c = 0; while (ustart[c + 1] <= u) c++; return c; };
        for (int c = 0; c < 4 * NC_MAX; c++) {
            if (c >= N) { P.tab[c] = make_uint2(0, 0); continue; }
            const int jj = c >> 2, u0 = ustart[c], nu = ustart[c + 1] - u0;
            const int k0 = kstart[jj], nk = kstart[jj + 1] - k0;
            const int h7 = (c / 7) & 15, mb7 = c % 7, hA = u0 >> 6, hB = (u0 + nu - 1) >> 6;
            const int ns = owner(h7 * 64 + 63) - owner(h7 * 64) + 1;
            P.tab[c].x = u0 | (nu << 10) | (k0 << 14) | (nk << 23);
            P.tab[c].y = h7 | (mb7 << 4) | ((c - owner(hA * 64)) << 8) | ((c - owner(hB * 64)) << 12) | (ns << 16);
        }
        cfg.gridDim = dim3(4 * s_nc);
        cudaLaunchKernelEx(&cfg, fused_kernel, P);
        return;
    }
    fb_q<<<16, 256, 0, st>>>(x, wq);
    fb_qabs<<<2048, 256, 0, st>>>(wuk);
    fb_scores<<<1024, 256, 0, st>>>(ckv);
    fb_softmax<<<16, 1024, 0, st>>>();
    fb_pv<<<dim3(64, 4), 256, 0, st>>>(ckv);
    fb_ctx<<<16, 256, 0, st>>>(wuv);
    fb_o<<<14, 256, 0, st>>>(x, wo);
    fb_gu<<<28, 64, 0, st>>>(wg, wu);
    fb_down<<<14, 256, 0, st>>>(wd, out);
}
```

```cpp
#include <cuda_runtime.h>
#include <cuda_bf16.h>
#include <cuda.h>
#include <stdint.h>
#include <limits.h>

namespace {

constexpr int NC_MAX = 32, NC_MIN = 29;
constexpr int NTHR = 512;

constexpr uint32_t UNIT = 8192;
constexpr uint32_t OFF_CKV = 0;
constexpr uint32_t OFF_WA = 18 * UNIT;
constexpr uint32_t OFF_X = OFF_WA + 9 * UNIT;
constexpr uint32_t OFF_SLOT = OFF_X;
constexpr uint32_t OFF_PBUF = OFF_X + 3 * 2048;
constexpr uint32_t PSTRIDE = 1088;
constexpr uint32_t OFF_BAR = OFF_PBUF + 4 * PSTRIDE;
constexpr uint32_t OFF_MISC = OFF_BAR + 42 * 8;
constexpr uint32_t OFF_WGT = OFF_CKV + 10 * UNIT;
constexpr uint32_t OFF_REF = OFF_MISC + 16;
constexpr uint32_t OFF_PVC = OFF_REF + 48;
constexpr uint32_t SMEM_BYTES = OFF_PVC + 64;
constexpr uint32_t OFF_QST = OFF_PBUF;
constexpr uint32_t OFF_TILE = OFF_X;
constexpr uint32_t OFF_CTX = OFF_X + 9216;
constexpr uint32_t OFF_AFR = OFF_X + 9728;
constexpr uint32_t OFF_H = OFF_X;
constexpr uint32_t OFF_GU = OFF_X + 1024;
static_assert(OFF_AFR + 576 <= OFF_BAR, "staging overflow");
static_assert(SMEM_BYTES + 128 <= 232448, "smem overflow");

enum { B_S0 = 26, B_P0 = 31, B_H = 37, B_GU = 38, G_P1 = 39, G_QA = 40, NBARS = 41 };
constexpr uint32_t OFF_PHASE = OFF_BAR + 41 * 8;

struct __align__(64) Params {
    CUtensorMap wq, wuk, ckv, wuv, wo, wg, wu, wd;
    const __nv_bfloat16* x;
    __nv_bfloat16* out;
    int NC;
    int W;
    unsigned dly;
    int RS;
    uint2 tab[4 * NC_MAX];
};

constexpr uint32_t MB1 = 0;
constexpr uint32_t MB2 = MB1 + 112 * 1024;
constexpr uint32_t MB3 = MB2 + 32768;
constexpr uint32_t MBM = MB3 + 1024 * 1024;
constexpr uint32_t MB4 = MBM + 16384;
constexpr uint32_t MB5 = MB4 + 16 * 12 * 1024;
constexpr uint32_t MB6 = MB5 + 16 * 1792;
constexpr uint32_t MB_SET = (MB6 + 4 * 28 * 28 * 32 + 1023) / 1024 * 1024;
__device__ __align__(1024) unsigned char g_mb[2 * MB_SET];
__device__ unsigned g_epoch;
#define TRACE(i) do {} while (0)

constexpr int SPIN_LIMIT = 1 << 18;
#define FIRSTPOLL 4
#define BACKOFF 0

__device__ __forceinline__ void mbar_init(uint32_t b, uint32_t c) {
    asm volatile("mbarrier.init.shared::cta.b64 [%0], %1;" ::"r"(b), "r"(c) : "memory");
}
__device__ __forceinline__ void mbar_expect(uint32_t b, uint32_t bytes) {
    asm volatile("mbarrier.arrive.expect_tx.shared::cta.b64 _, [%0], %1;" ::"r"(b), "r"(bytes) : "memory");
}
__device__ __forceinline__ void mbar_arrive(uint32_t b) {
    asm volatile("mbarrier.arrive.shared::cta.b64 _, [%0];" ::"r"(b) : "memory");
}
__device__ __forceinline__ bool mbar_try(uint32_t b, uint32_t ph) {
    uint32_t ok;
    asm volatile("{.reg .pred p; mbarrier.try_wait.parity.shared::cta.b64 p, [%1], %2; selp.u32 %0,1,0,p;}"
                 : "=r"(ok) : "r"(b), "r"(ph) : "memory");
    return ok;
}
__device__ __forceinline__ bool mbar_test(uint32_t b, uint32_t ph) {
    uint32_t ok;
    asm volatile("{.reg .pred p; mbarrier.test_wait.parity.shared::cta.b64 p, [%1], %2; selp.u32 %0,1,0,p;}"
                 : "=r"(ok) : "r"(b), "r"(ph) : "memory");
    return ok;
}
__device__ __forceinline__ bool mbar_try_cl(uint32_t b, uint32_t ph) {
    uint32_t ok;
    asm volatile("{.reg .pred p; mbarrier.try_wait.parity.acquire.cluster.shared::cta.b64 p, [%1], %2; selp.u32 %0,1,0,p;}"
                 : "=r"(ok) : "r"(b), "r"(ph) : "memory");
    return ok;
}
__device__ __forceinline__ void mbar_wait(uint32_t b, uint32_t ph) {
#pragma unroll 1
    for (int i = 0; i < SPIN_LIMIT; i++)
        if (mbar_try(b, ph)) return;
}
__device__ __forceinline__ void mbar_wait_cl(uint32_t b, uint32_t ph) {
#pragma unroll 1
    for (int i = 0; i < SPIN_LIMIT; i++)
        if (mbar_try_cl(b, ph)) return;
}
__device__ __forceinline__ void tma2p(uint32_t dst, const CUtensorMap* m, int x, int y, uint32_t bar, unsigned long long pol) {
    asm volatile("cp.async.bulk.tensor.2d.shared::cluster.global.mbarrier::complete_tx::bytes.L2::cache_hint [%0], [%1, {%3, %4}], [%2], %5;"
                 ::"r"(dst), "l"(m), "r"(bar), "r"(x), "r"(y), "l"(pol) : "memory");
}
__device__ __forceinline__ void tma3p(uint32_t dst, const CUtensorMap* m, int x, int y, int z, uint32_t bar, unsigned long long pol) {
    asm volatile("cp.async.bulk.tensor.3d.shared::cluster.global.mbarrier::complete_tx::bytes.L2::cache_hint [%0], [%1, {%3, %4, %5}], [%2], %6;"
                 ::"r"(dst), "l"(m), "r"(bar), "r"(x), "r"(y), "r"(z), "l"(pol) : "memory");
}
__device__ __forceinline__ uint32_t mapa(uint32_t a, uint32_t rank) {
    uint32_t r;
    asm("mapa.shared::cluster.u32 %0, %1, %2;" : "=r"(r) : "r"(a), "r"(rank));
    return r;
}
__device__ __forceinline__ void st_async_v4(uint32_t a, uint32_t x, uint32_t y, uint32_t z, uint32_t w, uint32_t bar) {
    asm volatile("st.async.weak.shared::cluster.mbarrier::complete_tx::bytes.v4.b32 [%0], {%1,%2,%3,%4}, [%5];"
                 ::"r"(a), "r"(x), "r"(y), "r"(z), "r"(w), "r"(bar) : "memory");
}
__device__ __forceinline__ void st_async_b32(uint32_t a, uint32_t x, uint32_t bar) {
    asm volatile("st.async.weak.shared::cluster.mbarrier::complete_tx::bytes.b32 [%0], %1, [%2];"
                 ::"r"(a), "r"(x), "r"(bar) : "memory");
}
__device__ __forceinline__ void ldsm4(uint32_t a, uint32_t& r0, uint32_t& r1, uint32_t& r2, uint32_t& r3) {
    asm volatile("ldmatrix.sync.aligned.m8n8.x4.shared.b16 {%0,%1,%2,%3}, [%4];"
                 : "=r"(r0), "=r"(r1), "=r"(r2), "=r"(r3) : "r"(a) : "memory");
}
__device__ __forceinline__ void ldsm4t(uint32_t a, uint32_t& r0, uint32_t& r1, uint32_t& r2, uint32_t& r3) {
    asm volatile("ldmatrix.sync.aligned.m8n8.x4.trans.shared.b16 {%0,%1,%2,%3}, [%4];"
                 : "=r"(r0), "=r"(r1), "=r"(r2), "=r"(r3) : "r"(a) : "memory");
}
__device__ __forceinline__ void mma16816(float (&c)[4], uint32_t a0, uint32_t a1, uint32_t a2, uint32_t a3, uint32_t b0, uint32_t b1) {
    asm("mma.sync.aligned.m16n8k16.row.col.f32.bf16.bf16.f32 {%0,%1,%2,%3}, {%4,%5,%6,%7}, {%8,%9}, {%0,%1,%2,%3};"
                 : "+f"(c[0]), "+f"(c[1]), "+f"(c[2]), "+f"(c[3]) : "r"(a0), "r"(a1), "r"(a2), "r"(a3), "r"(b0), "r"(b1));
}
__device__ __forceinline__ uint4 lds128(uint32_t a) {
    uint4 v;
    asm volatile("ld.shared.v4.u32 {%0,%1,%2,%3}, [%4];" : "=r"(v.x), "=r"(v.y), "=r"(v.z), "=r"(v.w) : "r"(a) : "memory");
    return v;
}
__device__ __forceinline__ uint32_t lds32(uint32_t a) {
    uint32_t v;
    asm volatile("ld.shared.u32 %0, [%1];" : "=r"(v) : "r"(a) : "memory");
    return v;
}
__device__ __forceinline__ uint32_t lds32_acq(uint32_t a) {
    uint32_t v;
    asm volatile("ld.volatile.shared.u32 %0, [%1];" : "=r"(v) : "r"(a) : "memory");
    return v;
}
__device__ __forceinline__ uint4 lds128_vol(uint32_t a) {
    uint4 v;
    asm volatile("ld.volatile.shared.v4.u32 {%0,%1,%2,%3}, [%4];" : "=r"(v.x), "=r"(v.y), "=r"(v.z), "=r"(v.w) : "r"(a) : "memory");
    return v;
}
__device__ __forceinline__ void sts128_vol(uint32_t a, uint4 v) {
    asm volatile("st.volatile.shared.v4.u32 [%0], {%1,%2,%3,%4};" ::"r"(a), "r"(v.x), "r"(v.y), "r"(v.z), "r"(v.w) : "memory");
}
__device__ __forceinline__ void sts32_rel(uint32_t a, uint32_t v) {
    asm volatile("st.release.cta.shared.u32 [%0], %1;" ::"r"(a), "r"(v) : "memory");
}
__device__ __forceinline__ void red_add_rel(uint32_t a, uint32_t v) {
    asm volatile("red.relaxed.cta.shared.add.u32 [%0], %1;" ::"r"(a), "r"(v) : "memory");
}
__device__ __forceinline__ void pv_wait(uint32_t pvc, int k) {
#pragma unroll 1
    for (int it = 0; it < SPIN_LIMIT * 8; it++)
        if ((int)lds32_acq(pvc + k * 4) >= 8) return;
}
__device__ __forceinline__ void sts128(uint32_t a, uint4 v) {
    asm volatile("st.shared.v4.u32 [%0], {%1,%2,%3,%4};" ::"r"(a), "r"(v.x), "r"(v.y), "r"(v.z), "r"(v.w) : "memory");
}
__device__ __forceinline__ void sts32(uint32_t a, uint32_t v) {
    asm volatile("st.shared.u32 [%0], %1;" ::"r"(a), "r"(v) : "memory");
}
__device__ __forceinline__ void sts16(uint32_t a, uint16_t v) {
    asm volatile("st.shared.u16 [%0], %1;" ::"r"(a), "h"(v) : "memory");
}
__device__ __forceinline__ void bar_sync(int id, int n) {
    asm volatile("bar.sync %0, %1;" ::"r"(id), "r"(n) : "memory");
}
__device__ __forceinline__ float bf16r(float v) { return __bfloat162float(__float2bfloat16_rn(v)); }
__device__ __forceinline__ uint32_t pack2(float lo, float hi) {
    __nv_bfloat162 t = __floats2bfloat162_rn(lo, hi);
    return *reinterpret_cast<uint32_t*>(&t);
}
__device__ __forceinline__ float bflo(uint32_t w) { return __uint_as_float(w << 16); }
__device__ __forceinline__ float bfhi(uint32_t w) { return __uint_as_float(w & 0xffff0000u); }
__device__ __forceinline__ float ex2(float x) {
    float y;
    asm("ex2.approx.ftz.f32 %0, %1;" : "=f"(y) : "f"(x));
    return y;
}
__device__ __forceinline__ uint32_t ldg_early(const uint32_t* p) {
    uint32_t v;
    asm volatile("ld.global.nc.u32 %0, [%1];" : "=r"(v) : "l"(p));
    return v;
}

__device__ __forceinline__ void backoff() {
    if (BACKOFF) {
        const uint32_t t0 = clock();
        while (clock() - t0 < BACKOFF) {}
    }
}
__device__ __forceinline__ void mb_st2(unsigned char* p, uint32_t a, uint32_t b) {
    asm volatile("st.relaxed.gpu.global.v2.u32 [%0], {%1,%2};" ::"l"(p), "r"(a), "r"(b) : "memory");
}
__device__ __forceinline__ void mb_st1(unsigned char* p, uint32_t a) {
    asm volatile("st.relaxed.gpu.global.u32 [%0], %1;" ::"l"(p), "r"(a) : "memory");
}
__device__ __forceinline__ void mb_put2(unsigned char* p, uint32_t a, uint32_t b) { mb_st2(p, a == 0u ? 0x80000000u : a, b); }
__device__ __forceinline__ void mb_put2f(unsigned char* p, float a, float b) { mb_put2(p, __float_as_uint(a), __float_as_uint(b)); }
__device__ __forceinline__ void mb_clear2(uint32_t off) {
    mb_st2(g_mb + off, 0u, 0u);
    mb_st2(g_mb + MB_SET + off, 0u, 0u);
}
__device__ __forceinline__ uint4 mb_ld4(const unsigned char* p) {
    uint4 v;
    asm volatile("ld.relaxed.gpu.global.v4.u32 {%0,%1,%2,%3}, [%4];" : "=r"(v.x), "=r"(v.y), "=r"(v.z), "=r"(v.w) : "l"(p) : "memory");
    return v;
}
template <int N, int STRIDE>
__device__ __forceinline__ void mb_poll(const unsigned char* p, int n, uint4 (&v)[N]) {
#pragma unroll
    for (int i = 0; i < N; i++) v[i] = i < n ? mb_ld4(p + i * STRIDE) : make_uint4(0, 0, 0, 0);
#pragma unroll 1
    for (int it = 0; it < SPIN_LIMIT; it++) {
        uint32_t m = 0xffffffffu;
#pragma unroll
        for (int i = 0; i < N; i++)
            if (i < n) m = min(m, min(v[i].x, v[i].z));
        if (m != 0u) break;
#pragma unroll
        for (int i = 0; i < N; i++)
            if (i < n && (N > 4 || min(v[i].x, v[i].z) == 0u)) v[i] = mb_ld4(p + i * STRIDE);
    }
}
__device__ __forceinline__ void delay(uint32_t clks) {
    const uint32_t t0 = clock();
    while (clock() - t0 < clks) {}
}

template <int N, int STRIDE>
__device__ __forceinline__ void mb_first(const unsigned char* p, int n, uint4 (&v)[N]) {
#pragma unroll
    for (int i = 0; i < N; i++) v[i] = i < n ? mb_ld4(p + i * STRIDE) : make_uint4(0, 0, 0, 0);
}
template <int N, int STRIDE>
__device__ __forceinline__ void mb_finish(const unsigned char* p, int n, uint4 (&v)[N]) {
#pragma unroll 1
    for (int it = 0; it < SPIN_LIMIT; it++) {
        uint32_t m = 0xffffffffu;
#pragma unroll
        for (int i = 0; i < N; i++)
            if (i < n) m = min(m, min(v[i].x, v[i].z));
        if (m != 0u) break;
#pragma unroll
        for (int i = 0; i < N; i++)
            if (i < n) v[i] = mb_ld4(p + i * STRIDE);
    }
}

__device__ __forceinline__ void ln_stats(const float (&v)[14], float& mb, float& den) {
    float s = 0.f;
#pragma unroll
    for (int i = 0; i < 14; i++) s += v[i];
#pragma unroll
    for (int o = 16; o; o >>= 1) s += __shfl_xor_sync(~0u, s, o);
    const float mean = s * (1.f / 448.f);
    float q = 0.f;
#pragma unroll
    for (int i = 0; i < 14; i++) { const float d = v[i] - mean; q += d * d; }
#pragma unroll
    for (int o = 16; o; o >>= 1) q += __shfl_xor_sync(~0u, q, o);
    mb = bf16r(mean);
    den = bf16r(__fsqrt_rn(bf16r(bf16r(q * (1.f / 448.f)) + 1e-5f)));
}
__device__ __forceinline__ void ln_stats1(const float (&v)[14], float c, float& mb, float& den) {
    float s0 = 0.f, s1 = 0.f, q0 = 0.f, q1 = 0.f;
#pragma unroll
    for (int i = 0; i < 7; i++) {
        const float d0 = v[2 * i] - c, d1 = v[2 * i + 1] - c;
        s0 += d0; s1 += d1; q0 += d0 * d0; q1 += d1 * d1;
    }
    float s = s0 + s1, q = q0 + q1;
#pragma unroll
    for (int o = 16; o; o >>= 1) { s += __shfl_xor_sync(~0u, s, o); q += __shfl_xor_sync(~0u, q, o); }
    const float md = s * (1.f / 448.f);
    mb = bf16r(c + md);
    den = bf16r(__fsqrt_rn(bf16r(bf16r(fmaxf(q * (1.f / 448.f) - md * md, 0.f)) + 1e-5f)));
}
__device__ __forceinline__ float ln_apply(float v, float mb, float den) { return __fdiv_rn(bf16r(v - mb), den); }
__device__ __forceinline__ float ln_apply_r(float v, float mb, float rden) { return bf16r(v - mb) * rden; }

__device__ __forceinline__ uint32_t frag_off(int w) {
    const int s = w >> 3, half = (w >> 2) & 1, t = w & 3;
    return (uint32_t)((((s >> 1) * 4 + t) * 4 + (s & 1) * 2 + half) * 4);
}
__device__ __forceinline__ int f2o(float f) { const int i = __float_as_int(f); return i ^ ((i >> 31) & 0x7fffffff); }
__device__ __forceinline__ float o2f(int i) { return __int_as_float(i ^ ((i >> 31) & 0x7fffffff)); }

__device__ __forceinline__ uint32_t mb_ld1(const unsigned char* p) {
    uint32_t v;
    asm volatile("ld.relaxed.gpu.global.u32 %0, [%1];" : "=r"(v) : "l"(p) : "memory");
    return v;
}
__device__ __forceinline__ void combine_unit(uint32_t SB, const unsigned char* src, const unsigned char* msrc, int n, bool mact,
                                             uint4 (&v)[2], uint32_t mj, int ul, int lane) {
#pragma unroll 1
    for (int it = 0; it < SPIN_LIMIT; it++) {
        uint32_t m = mj;
        if (n > 0) m = min(m, min(v[0].x, v[0].z));
        if (n > 1) m = min(m, min(v[1].x, v[1].z));
        if (m != 0u) break;
        if (n > 0 && min(v[0].x, v[0].z) == 0u) v[0] = mb_ld4(src);
        if (n > 1 && min(v[1].x, v[1].z) == 0u) v[1] = mb_ld4(src + 512);
        if (mj == 0u) mj = mb_ld1(msrc);
    }
    __syncwarp();
    const uint32_t tile = SB + OFF_TILE + ul * 1024, wgt = SB + OFF_WGT + ul * 128;
    sts128(tile + lane * 16, v[0]);
    sts128(tile + 512 + lane * 16, v[1]);
    {
        const float mf = __uint_as_float(mj);
        const float w = ex2(mf - o2f(__reduce_max_sync(~0u, f2o(mf))));
        const int jj = lane & 15;
        const uint32_t d = wgt + ((lane >> 4) * 4 + ((jj & 7) >> 1)) * 16 + (jj >> 3) * 8 + (jj & 1) * 2;
        const __nv_bfloat16 hi = __float2bfloat16_rn(w), lo = __float2bfloat16_rn(w - __bfloat162float(hi));
        sts16(d, *reinterpret_cast<const uint16_t*>(&hi));
        sts16(d + 4, *reinterpret_cast<const uint16_t*>(&lo));
    }
    __syncwarp();
    const int t = lane & 3;
    uint32_t b[8];
    const uint32_t ts = tile + ((lane & 7) + (lane & 8)) * 32 + (lane >> 4) * 16;
    ldsm4t(ts, b[0], b[1], b[2], b[3]);
    ldsm4t(ts + 512, b[4], b[5], b[6], b[7]);
    const uint4 w0 = lds128(wgt + t * 16), w1 = lds128(wgt + 64 + t * 16);
    float c0[4] = {}, c1[4] = {}, c2[4] = {}, c3[4] = {};
    mma16816(c0, w0.x, w0.y, w0.z, w0.w, b[0], b[1]);
    mma16816(c1, w0.x, w0.y, w0.z, w0.w, b[2], b[3]);
    mma16816(c2, w1.x, w1.y, w1.z, w1.w, b[4], b[5]);
    mma16816(c3, w1.x, w1.y, w1.z, w1.w, b[6], b[7]);
    const float v0 = (c0[0] + c0[2]) + (c2[0] + c2[2]), v1 = (c0[1] + c0[3]) + (c2[1] + c2[3]);
    const float v2 = (c1[0] + c1[2]) + (c3[0] + c3[2]), v3 = (c1[1] + c1[3]) + (c3[1] + c3[3]);
    const uint32_t a0 = pack2(v0, v1), a2 = pack2(v2, v3);
    const uint32_t a1 = pack2(v0 - bflo(a0), v1 - bfhi(a0)), a3 = pack2(v2 - bflo(a2), v3 - bfhi(a2));
    if (lane < 4) sts128(SB + OFF_AFR + ul * 64 + t * 16, make_uint4(a0, a1, a2, a3));
}

__global__ void __launch_bounds__(NTHR, 1) fused_kernel(const __grid_constant__ Params P) {
    extern __shared__ __align__(1024) unsigned char smem_raw[];
    const uint32_t SB = (uint32_t)__cvta_generic_to_shared(smem_raw);
    const int tid = threadIdx.x, warp = tid >> 5, lane = tid & 31;
    const int g = lane >> 2, t = lane & 3;
    const int cta = blockIdx.x, j = cta >> 2, r = cta & 3;
    const uint2 tab = P.tab[cta];
    const int u0 = tab.x & 1023, nu = (tab.x >> 10) & 15, k0 = (tab.x >> 14) & 511, nk = (tab.x >> 23) & 31;
    const int h7 = tab.y & 15, mb7 = (tab.y >> 4) & 7;
    const bool full = cta < 112;
    const int nug = (nu + 1) >> 1, nb = (nk + 1) >> 1;
    const int g_uk = full ? 2 : 0, g_kv = g_uk + nug, g_uv = g_kv + nb, g_wo = g_uv + nug, g_gu = g_wo + 2, g_wd = g_gu + 2;
    auto BAR = [&](int i) -> uint32_t { return SB + OFF_BAR + 8 * i; };

    if (warp == 11) {
        const int W1 = P.W & 15, W2 = (P.W >> 4) & 15, W3 = (P.W >> 8) & 15, W4 = (P.W >> 12) & 15, W0 = (P.W >> 20) & 15, ngroups = full ? g_wd + 1 : g_wo;
        int done = 0;
        unsigned long long pol;
        asm volatile("createpolicy.fractional.L2::evict_first.b64 %0, 1.0;" : "=l"(pol));
        if (lane < 8) asm volatile("prefetch.tensormap [%0];" ::"l"(reinterpret_cast<const char*>(&P) + lane * 128) : "memory");
        if (lane == 0) {
            mbar_init(BAR(0), 1);
            mbar_init(BAR(1), 1);
            mbar_init(BAR(2), 1);
            mbar_init(BAR(3), 1);
            asm volatile("fence.mbarrier_init.release.cluster;" ::: "memory");
        }
        __syncwarp();
#pragma unroll 1
        for (int gi = 0; gi < ngroups; gi++) {
            if (gi == min(W1, 4)) {
                __syncthreads();
                asm volatile("barrier.cluster.arrive.relaxed.aligned;" ::: "memory");
            }
            const CUtensorMap* map;
            uint32_t dst, dstep = UNIT;
            int n = 2, x0 = 0, y0, z0 = -1, x1 = 0, y1, z1 = 0, gate = -1, pvgate = 0;
            if (gi < g_uk) {
                map = &P.wq; dst = OFF_CKV + (14 + 2 * gi) * UNIT;
                y0 = mb7 * 64 + gi * 32; y1 = y0 + 16; z0 = z1 = h7 * 4;
            } else if (gi < g_kv || (gi >= g_uv && gi < g_wo)) {
                const bool uv = gi >= g_uv;
                const int i0 = 2 * (gi - (uv ? g_uv : g_uk)), u = u0 + i0;
                if (gi == g_uv) gate = G_QA;
                map = uv ? &P.wuv : &P.wuk; dst = OFF_WA + i0 * UNIT; n = min(2, nu - i0);
                y0 = (u & 63) * 16; z0 = (u >> 6) * 4; y1 = ((u + 1) & 63) * 16; z1 = ((u + 1) >> 6) * 4;
            } else if (gi < g_uv) {
                const int b = gi - g_kv;
                if (b == 7 && full) gate = G_P1;
                map = &P.ckv; dst = OFF_CKV + 2 * b * UNIT; n = min(2, nk - 2 * b);
                y0 = (k0 + 2 * b) * 16; y1 = y0 + 16; z0 = z1 = r * 4;
            } else if (gi < g_gu) {
                const int i = gi - g_wo;
                pvgate = max(1, nb - (int)((P.W >> 16) & 15));
                map = &P.wo; dst = OFF_CKV + 2 * i * UNIT;
                x0 = x1 = mb7 * 64; y0 = h7 * 256 + i * 128; y1 = y0 + 64;
            } else if (gi < g_wd) {
                const int i = gi - g_gu;
                pvgate = 3;
                map = (r & 1) ? &P.wu : &P.wg; dst = OFF_CKV + 4 * UNIT + i * 14336; n = 1; dstep = 14336;
                x0 = j * 64; y0 = (r >> 1) * 224 + i * 112; y1 = 0;
            } else {
                pvgate = 4;
                map = &P.wd; dst = OFF_CKV + 8 * UNIT;
                x0 = r * 112; x1 = x0 + 64; y0 = y1 = j * 64;
            }
            if (gate >= 0) mbar_wait(BAR(gate), 0);
            if (pvgate) pv_wait(SB + OFF_PVC, pvgate);
            {
                const int W = gi < g_kv ? W1 : gi < g_uv ? W2 : gi < g_wo ? W3 : W4;
#pragma unroll 1
                for (; done <= gi - W; done++) mbar_wait(BAR(done), 0);
                if (gi >= g_kv && gi < g_uv) {
#pragma unroll 1
                    for (; done <= gi - W0 && !mbar_test(BAR(G_QA), 0); done++) mbar_wait(BAR(done), 0);
                }
            }
            if (lane == 0) {
                const uint32_t bar = BAR(gi);
                mbar_expect(bar, n * dstep);
                if (z0 >= 0) {
                    tma3p(SB + dst, map, 0, y0, z0, bar, pol);
                    if (n > 1) tma3p(SB + dst + UNIT, map, 0, y1, z1, bar, pol);
                } else {
                    tma2p(SB + dst, map, x0, y0, bar, pol);
                    if (n > 1) tma2p(SB + dst + UNIT, map, x1, y1, bar, pol);
                }
                if (gi == g_kv) TRACE(15);
                if (gi == g_uv) TRACE(19);
                if (gi == g_wo) TRACE(20);
            }
            __syncwarp();
        }
        if (lane == 0) TRACE(31);
        asm volatile("barrier.cluster.wait.acquire.aligned;" ::: "memory");
        return;
    }

    uint32_t epoch, xr[7], xa[8], xw0, xw1;
    {
        const uint32_t* x32 = reinterpret_cast<const uint32_t*>(P.x);
        asm volatile("ld.relaxed.gpu.global.u32 %0, [%1];" : "=r"(epoch) : "l"(&g_epoch) : "memory");
#pragma unroll
        for (int i = 0; i < 7; i++) xr[i] = ldg_early(x32 + lane + 32 * i);
#pragma unroll
        for (int i = 0; i < 8; i++) xa[i] = ldg_early(x32 + mb7 * 32 + (i >> 1) * 8 + (i & 1) * 4 + t);
        xw0 = ldg_early(x32 + r * 56 + 2 * min(lane, 27));
        xw1 = ldg_early(x32 + r * 56 + 2 * min(lane, 27) + 1);
    }
    if (lane == 0) {
#pragma unroll 1
        for (int i = 4 + (warp > 11 ? warp - 1 : warp); i < NBARS; i += 15) mbar_init(BAR(i), i == G_P1 ? 8 : i == G_QA ? 4 : i == B_GU ? 2 : 1);
        if (warp >= 8 && warp < 11) sts128(SB + OFF_REF + (warp - 8) * 16, make_uint4(0, 0, 0, 0));
        if (warp >= 12) sts128(SB + OFF_PVC + (warp - 12) * 16, make_uint4(0, 0, 0, 0));
        if (warp == 12) sts32(SB + OFF_PHASE, 0);
        asm volatile("fence.mbarrier_init.release.cluster;" ::: "memory");
    }
    __syncthreads();
    asm volatile("barrier.cluster.arrive.relaxed.aligned;" ::: "memory");
    const int NC = P.NC;
    const int hA = u0 >> 6, hB = (u0 + nu - 1) >> 6;
    const int RS = P.RS, RP = RS + 1;
    const uint32_t xoff = nk <= 17 ? OFF_CKV + 17 * UNIT : OFF_WA + 8 * UNIT;
    auto slot_off = [&](int i) -> uint32_t { return i < 3 ? OFF_SLOT + i * 2048 : xoff + (i - 3) * 2048; };
    auto p_off = [&](int i) -> uint32_t { return i < 4 ? OFF_PBUF + i * PSTRIDE : xoff + 4096 + (i - 4) * PSTRIDE; };

    if (warp >= 12) {
        const int nt = warp - 12;
        const uint32_t s_dst = mapa(SB + r * 512 + (nt * 2 + (g >> 2)) * 64 + t * 16, g & 3);
        const uint32_t s_bar = mapa(BAR(B_S0), g & 3);
        const int srow = (nt & 1) * 8 + (lane & 7);
        const uint32_t s_src0 = SB + OFF_CKV + (nt >> 1) * UNIT + srow * 128 + (((lane >> 3) ^ (srow & 7)) << 4);
        const uint32_t s_src1 = SB + OFF_CKV + (nt >> 1) * UNIT + srow * 128 + (((4 + (lane >> 3)) ^ (srow & 7)) << 4);
        unsigned char* const mb = g_mb + (epoch & 1) * MB_SET;
        const int ht = tid - 384;
        bar_sync(13, 384);
        delay((P.dly & 31) * 64);
        if (ht < 64 || hB != hA) {
            const int i = ht & 63, hs = ht >> 6;
            uint4 v[7];
            mb_poll<7, 1024>(mb + MB1 + (hs ? hB : hA) * 7168 + i * 16, 7, v);
            float a0 = 0.f, a1 = 0.f, a2 = 0.f, a3 = 0.f;
#pragma unroll
            for (int k = 0; k < 7; k++) {
                a0 += __uint_as_float(v[k].x); a1 += __uint_as_float(v[k].y);
                a2 += __uint_as_float(v[k].z); a3 += __uint_as_float(v[k].w);
            }
            const uint32_t d = SB + OFF_QST + hs * 512 + frag_off(2 * i);
            sts32(d, pack2(a0, a1));
            sts32(d + 16, pack2(a2, a3));
        }
        asm volatile("bar.arrive 7, 384;" ::: "memory");
        asm volatile("barrier.cluster.wait.acquire.aligned;" ::: "memory");
        {
            bar_sync(6, 384);
            delay(((P.dly >> 5) & 31) * 64);
            uint4 v[4];
            mb_poll<4, 2048>(mb + MB2 + r * 8192 + ht * 16, 4, v);
            const uint32_t a = SB + OFF_WA + ((ht >> 1) & 15) * 512 + ((ht >> 5) * 4 + (ht & 1) * 2) * 16;
            sts128(a, make_uint4(v[0].x, v[2].x, v[0].y, v[2].y));
            sts128(a + 16, make_uint4(v[0].z, v[2].z, v[0].w, v[2].w));
            sts128(a + 256, make_uint4(v[1].x, v[3].x, v[1].y, v[3].y));
            sts128(a + 272, make_uint4(v[1].z, v[3].z, v[1].w, v[3].w));
            bar_sync(9, 128);
        }
        if (ht == 0) TRACE(4);
        uint32_t qa[16][4];
#pragma unroll
        for (int s = 0; s < 16; s++) {
            const uint4 q = lds128(SB + OFF_WA + s * 512 + lane * 16);
            qa[s][0] = q.x; qa[s][1] = q.y; qa[s][2] = q.z; qa[s][3] = q.w;
        }
        __syncwarp();
        if (lane == 0) mbar_arrive(BAR(G_QA));
        const int nbs = (nk - (nt >> 1) + 1) >> 1;
        int sb = 0;
#pragma unroll 1
        for (int b = 0; b < nbs; b++) {
            mbar_wait(BAR(g_kv + b), 0);
            float c0[4] = {}, c1[4] = {}, c2[4] = {}, c3[4] = {};
#pragma unroll
            for (int i = 0; i < 4; i++) {
                uint32_t b0, b1, b2, b3, b4, b5, b6, b7;
                ldsm4(s_src0 + 2 * b * UNIT + i * 2048, b0, b1, b2, b3);
                ldsm4(s_src1 + 2 * b * UNIT + i * 2048, b4, b5, b6, b7);
                mma16816(c0, qa[4 * i][0], qa[4 * i][1], qa[4 * i][2], qa[4 * i][3], b0, b1);
                mma16816(c1, qa[4 * i + 1][0], qa[4 * i + 1][1], qa[4 * i + 1][2], qa[4 * i + 1][3], b2, b3);
                mma16816(c2, qa[4 * i + 2][0], qa[4 * i + 2][1], qa[4 * i + 2][2], qa[4 * i + 2][3], b4, b5);
                mma16816(c3, qa[4 * i + 3][0], qa[4 * i + 3][1], qa[4 * i + 3][2], qa[4 * i + 3][3], b6, b7);
            }
            if (b >= RS) pv_wait(SB + OFF_PVC, b - RS);
            st_async_v4(s_dst + slot_off(sb), __float_as_uint((c0[0] + c1[0]) + (c2[0] + c3[0])),
                        __float_as_uint((c0[1] + c1[1]) + (c2[1] + c3[1])), __float_as_uint((c0[2] + c1[2]) + (c2[2] + c3[2])),
                        __float_as_uint((c0[3] + c1[3]) + (c2[3] + c3[3])), s_bar + sb * 8);
            if (++sb == RS) sb = 0;
        }
        if (!full) return;
        if (nt < 2) {
            bar_sync(10, 320);
            delay(((P.dly >> 15) & 31) * 64);
            uint4 v[10];
            mb_poll<10, 1024>(mb + MB4 + h7 * 12288 + ht * 16, (tab.y >> 16) & 15, v);
            float a0 = 0.f, a1 = 0.f, a2 = 0.f, a3 = 0.f, e0 = 0.f, e1 = 0.f, e2 = 0.f, e3 = 0.f;
#pragma unroll
            for (int k = 0; k < 5; k++) {
                a0 += __uint_as_float(v[k].x); a1 += __uint_as_float(v[k].y);
                a2 += __uint_as_float(v[k].z); a3 += __uint_as_float(v[k].w);
                e0 += __uint_as_float(v[5 + k].x); e1 += __uint_as_float(v[5 + k].y);
                e2 += __uint_as_float(v[5 + k].z); e3 += __uint_as_float(v[5 + k].w);
            }
            bar_sync(4, 96);
            const float rl = __uint_as_float(lds32(SB + OFF_MISC));
            const uint32_t d = SB + OFF_CTX + frag_off(2 * ht);
            sts32(d, pack2((a0 + e0) * rl, (a1 + e1) * rl));
            sts32(d + 16, pack2((a2 + e2) * rl, (a3 + e3) * rl));
            asm volatile("bar.arrive 8, 320;" ::: "memory");
        } else if (nt == 2) {
            bar_sync(11, 288);
            delay(((P.dly >> 20) & 31) * 64);
            if (lane < 28) {
                const int w = (r & 1) * 56 + 2 * lane;
                const uint32_t d0 = SB + OFF_H + (r >> 1) * 448 + frag_off(w);
                uint32_t da[4], ba[4];
#pragma unroll
                for (int k = 0; k < 4; k++) { da[k] = mapa(d0, k); ba[k] = mapa(BAR(B_H), k); }
                uint4 v[16];
                mb_poll<16, 1792>(mb + MB5 + r * 448 + lane * 16, 16, v);
                float a[4][4] = {};
#pragma unroll
                for (int k = 0; k < 16; k++) {
                    a[k & 3][0] += __uint_as_float(v[k].x); a[k & 3][1] += __uint_as_float(v[k].y);
                    a[k & 3][2] += __uint_as_float(v[k].z); a[k & 3][3] += __uint_as_float(v[k].w);
                }
                const uint32_t h0 = pack2(bflo(xw0) + bf16r((a[0][0] + a[1][0]) + (a[2][0] + a[3][0])),
                                          bfhi(xw0) + bf16r((a[0][1] + a[1][1]) + (a[2][1] + a[3][1])));
                const uint32_t h1 = pack2(bflo(xw1) + bf16r((a[0][2] + a[1][2]) + (a[2][2] + a[3][2])),
                                          bfhi(xw1) + bf16r((a[0][3] + a[1][3]) + (a[2][3] + a[3][3])));
#pragma unroll
                for (int k = 0; k < 4; k++) {
                    st_async_b32(da[k], h0, ba[k]);
                    st_async_b32(da[k] + 16, h1, ba[k]);
                }
            }
        } else {
            const int k = (lane >> 1) & 3;
            mbar_wait(BAR(B_H), 0);
            {
                float v[14], mean, den;
#pragma unroll
                for (int i = 0; i < 7; i++) {
                    const uint32_t w = lds32(SB + OFF_H + (lane + 32 * i) * 4);
                    v[2 * i] = bflo(w); v[2 * i + 1] = bfhi(w);
                }
                ln_stats1(v, bflo(lds32(SB + OFF_H)), mean, den);
                if (lane == 0) {
                    sts32(SB + OFF_MISC + 8, __float_as_uint(mean));
                    sts32(SB + OFF_MISC + 12, __float_as_uint(__fdividef(1.f, den)));
                    mbar_arrive(BAR(B_GU));
                }
            }
            const uint32_t hw = lds32(SB + OFF_H + (r >> 1) * 448 + frag_off((r & 1) * 56 + j * 2 + (k >> 1)));
            uint4 v[4];
            const int n = lane < 4 ? 4 : lane < 8 ? 3 : 0;
            bar_sync(12, 288);
            delay(((P.dly >> 25) & 31) * 64);
            mb_poll<4, 256>(mb + MB6 + ((r * 28 + j) * 28 + lane) * 32, n, v);
            float v0 = (__uint_as_float(v[0].x) + __uint_as_float(v[1].x)) + (__uint_as_float(v[2].x) + __uint_as_float(v[3].x));
            float v1 = (__uint_as_float(v[0].y) + __uint_as_float(v[1].y)) + (__uint_as_float(v[2].y) + __uint_as_float(v[3].y));
            float v2 = (__uint_as_float(v[0].z) + __uint_as_float(v[1].z)) + (__uint_as_float(v[2].z) + __uint_as_float(v[3].z));
            float v3 = (__uint_as_float(v[0].w) + __uint_as_float(v[1].w)) + (__uint_as_float(v[2].w) + __uint_as_float(v[3].w));
            __syncwarp();
            const bool up = lane & 4;
            const float s0 = up ? v0 : v2, s1 = up ? v1 : v3;
            const float k0v = up ? v2 : v0, k1v = up ? v3 : v1;
            v0 = k0v + __shfl_xor_sync(~0u, s0, 4);
            v1 = k1v + __shfl_xor_sync(~0u, s1, 4);
            const bool up2 = lane & 2;
            const float s2 = up2 ? v0 : v1, k2v = up2 ? v1 : v0;
            v0 = k2v + __shfl_xor_sync(~0u, s2, 2);
            v0 += __shfl_xor_sync(~0u, v0, 1);
            if (lane < 8 && (lane & 1) == 0)
                P.out[r * 112 + j * 4 + k] = __float2bfloat16_rn(((k & 1) ? bfhi(hw) : bflo(hw)) + bf16r(v0));
            if (cta == 0 && lane == 0) g_epoch = epoch + 1;
            if (lane == 0) TRACE(13);
        }
        return;
    }
    if (warp >= 8) {
        const int sb = warp - 8, nt = lane >> 3, gg = (lane >> 2) & 1;
        if (lane == 0) {
            mbar_expect(BAR(B_S0 + sb), 2048);
            if (sb + 3 < RS) mbar_expect(BAR(B_S0 + sb + 3), 2048);
        }
        const uint32_t dst_a = mapa(SB + (nt >> 1) * 512 + ((r + 4 * gg) * 4 + t) * 16, (nt & 1) * 2);
        const uint32_t dst_b = mapa(SB + (nt >> 1) * 512 + ((r + 4 * gg) * 4 + t) * 16, (nt & 1) * 2 + 1);
        const uint32_t bar_a = mapa(BAR(B_P0), (nt & 1) * 2), bar_b = mapa(BAR(B_P0), (nt & 1) * 2 + 1);
        const uint32_t dst_m = mapa(SB + 1024 + (r + 4 * gg + 8 * nt) * 4, t), bar_m = mapa(BAR(B_P0), t);
        const uint32_t ref_prev = SB + OFF_REF + (sb == 0 ? 2 : sb - 1) * 16;
        asm volatile("barrier.cluster.wait.acquire.aligned;" ::: "memory");
#pragma unroll 1
        for (int b = sb; b < nb; b += 3) {
            const int si = b >= RS ? (b >= 2 * RS ? b - 2 * RS : b - RS) : b, sph = (b >= RS && b < 2 * RS) ? 1 : 0;
            const int pi = b >= RP ? (b >= 2 * RP ? b - 2 * RP : b - RP) : b;
            const uint32_t po = p_off(pi), bo = pi * 8, sa = SB + slot_off(si) + lane * 16;
            const bool valid = 2 * b + (nt >> 1) < nk;
            if (b >= RS) {
                const uint32_t tk = SB + OFF_REF + ((b - RS) % 3) * 16;
#pragma unroll 1
                for (int it = 0; it < SPIN_LIMIT * 8; it++)
                    if ((int)(lds128_vol(tk).x & 15u) > b - RS) break;
            }
            mbar_wait(BAR(B_S0 + si), sph);
            if (lane == 0 && b == 5) TRACE(16);
            const uint4 v0 = lds128(sa), v1 = lds128(sa + 512), v2 = lds128(sa + 1024), v3 = lds128(sa + 1536);
            float s0 = (__uint_as_float(v0.x) + __uint_as_float(v1.x)) + (__uint_as_float(v2.x) + __uint_as_float(v3.x));
            float s1 = (__uint_as_float(v0.y) + __uint_as_float(v1.y)) + (__uint_as_float(v2.y) + __uint_as_float(v3.y));
            float s2 = (__uint_as_float(v0.z) + __uint_as_float(v1.z)) + (__uint_as_float(v2.z) + __uint_as_float(v3.z));
            float s3 = (__uint_as_float(v0.w) + __uint_as_float(v1.w)) + (__uint_as_float(v2.w) + __uint_as_float(v3.w));
            const int i0 = valid ? f2o(fmaxf(s0, s1)) : INT_MIN, i1 = valid ? f2o(fmaxf(s2, s3)) : INT_MIN;
            int ra = __reduce_max_sync(~0u, gg ? INT_MIN : i0), rb = __reduce_max_sync(~0u, gg ? i0 : INT_MIN);
            int rc = __reduce_max_sync(~0u, gg ? INT_MIN : i1), rd = __reduce_max_sync(~0u, gg ? i1 : INT_MIN);
            ra = (ra + 15) & ~15; rb = (rb + 15) & ~15; rc = (rc + 15) & ~15; rd = (rd + 15) & ~15;
            if (b > 0) {
                uint4 pr;
#pragma unroll 1
                for (int it = 0; it < SPIN_LIMIT * 8; it++) {
                    pr = lds128_vol(ref_prev);
                    if ((int)(pr.x & pr.y & pr.z & pr.w & 15u) == b && (int)((pr.x | pr.y | pr.z | pr.w) & 15u) == b) break;
                }
                ra = max(ra, (int)pr.x - b); rb = max(rb, (int)pr.y - b); rc = max(rc, (int)pr.z - b); rd = max(rd, (int)pr.w - b);
            }
            __syncwarp();
            if (lane == 0) sts128_vol(SB + OFF_REF + sb * 16, make_uint4(ra | (b + 1), rb | (b + 1), rc | (b + 1), rd | (b + 1)));
            const float n0 = o2f(gg ? rb : ra), n1 = o2f(gg ? rd : rc);
            const uint32_t w0 = pack2(ex2(s0 - n0), ex2(s1 - n0)), w1 = pack2(ex2(s2 - n1), ex2(s3 - n1));
            const uint32_t o0 = __shfl_xor_sync(~0u, w0, 8), o1 = __shfl_xor_sync(~0u, w1, 8);
            if (lane < 16) st_async_b32(dst_m + po, __float_as_uint(nt ? n1 : n0), bar_m + bo);
            if (valid) {
                const bool odd = nt & 1;
                const uint32_t x0 = odd ? o0 : w0, x1 = odd ? o1 : w1, x2 = odd ? w0 : o0, x3 = odd ? w1 : o1;
                st_async_v4(dst_a + po, x0, x1, x2, x3, bar_a + bo);
                st_async_v4(dst_b + po, x0, x1, x2, x3, bar_b + bo);
            }
            if (lane == 0 && b == 5) TRACE(17);
            if (lane == 0 && b + RS < nb) mbar_expect(BAR(B_S0 + si), (2 * (b + RS) + 1 < nk) ? 2048 : 1024);
        }
        if (sb == 2) {
            bar_sync(5, 320);
            const unsigned char* mbp = g_mb + (epoch & 1) * MB_SET;
            const unsigned char* src = mbp + MB3 + (u0 + 8) * 1024 + lane * 16;
            const unsigned char* msrc = mbp + MBM + (((u0 + 8) >> 6) * NC_MAX + lane) * 32;
            const int n = nu > 8 ? ((16 + (lane >> 1) < NC) ? 2 : 1) : 0;
            const bool mact = nu > 8 && lane < NC;
            uint4 v[2];
            delay(((P.dly >> 10) & 31) * 64);
            mb_first<2, 512>(src, n, v);
            const uint32_t mj = mact ? mb_ld1(msrc) : (nu > 8 ? 0xff800000u : 0x3f800000u);
            combine_unit(SB, src, msrc, n, mact, v, mj, 8, lane);
            asm volatile("bar.arrive 3, 288;" ::: "memory");
        } else if (sb == 1) {
            bar_sync(5, 320);
            if (full) {
                const unsigned char* pm = g_mb + (epoch & 1) * MB_SET + MBM + (h7 * NC_MAX + lane) * 32;
                uint2 a = make_uint2(0xff800000u, 0);
                if (lane < NC) {
#pragma unroll 1
                    for (int it = 0; it < SPIN_LIMIT; it++) {
                        asm volatile("ld.relaxed.gpu.global.v2.u32 {%0,%1}, [%2];" : "=r"(a.x), "=r"(a.y) : "l"(pm) : "memory");
                        if (a.x != 0u) break;
                        __nanosleep(200);
                    }
                }
                __syncwarp();
                const float mj = __uint_as_float(a.x);
                float L = ex2(mj - o2f(__reduce_max_sync(~0u, f2o(mj)))) * __uint_as_float(a.y);
#pragma unroll
                for (int o = 16; o; o >>= 1) L += __shfl_xor_sync(~0u, L, o);
                if (lane == 0) sts32(SB + OFF_MISC, __float_as_uint(__fdividef(1.f, L)));
                asm volatile("bar.arrive 4, 96;" ::: "memory");
            }
        }
        return;
    }

    if (tid == 0) {
#pragma unroll 1
        for (int i = 0; i < RP; i++) mbar_expect(BAR(B_P0 + i), 1088);
        mbar_expect(BAR(B_H), 896);
        mbar_expect(BAR(B_GU), 2048);
    }
    const uint32_t o1 = MB1 + cta * 1024 + warp * 128 + lane * 8;
    const uint32_t o3 = MB3 + ((g * 64 + r * 16 + warp * 2) * NC_MAX + j) * 32 + t * 8;
    const bool a4 = g < 4 || hB != hA;
    const uint32_t o4 = MB4 + ((g < 4 ? hA : hB) * 12 + ((tab.y >> (g < 4 ? 8 : 12)) & 15)) * 1024 + warp * 128 + (lane & 15) * 8;
    const uint32_t o5 = MB5 + h7 * 1792 + mb7 * 256 + warp * 32 + t * 8;
    const int li6 = (warp + 8 * (g & 1)) * 4 + t;
    const bool a6 = g < 4 && ((g & 1) == 0 || warp < 6);
    const uint32_t o6 = MB6 + ((r * 28 + (li6 >> 1)) * 28 + j) * 32 + (g >> 1) * 16 + (li6 & 1) * 8;
    const bool am = tid < 32 && (g & 3) == r;
    const uint32_t om = MBM + (g * NC_MAX + j) * 32 + t * 8;
    const int ua = u0 + warp, ub = u0 + 8;
    const uint32_t o2a = MB2 + ((((ua & 63) >> 4) * 16 + (ua >> 6)) * 16 + (ua & 15)) * 32 + (lane >> 3) * 8;
    const uint32_t o2b = MB2 + ((((ub & 63) >> 4) * 16 + (ub >> 6)) * 16 + (ub & 15)) * 32 + (lane >> 3) * 8;
    if (full && lane < 16) mb_clear2(o1);
    if ((lane & 7) == 0) {
        mb_clear2(o2a);
        if (warp == 0 && nu > 8) mb_clear2(o2b);
    }
    unsigned char* const mb = g_mb + (epoch & 1) * MB_SET;

    if (full) {
        float v[14];
#pragma unroll
        for (int i = 0; i < 7; i++) { v[2 * i] = bflo(xr[i]); v[2 * i + 1] = bfhi(xr[i]); }
        float mean, den;
        ln_stats(v, mean, den);
        const float rden = __frcp_rn(den);
#pragma unroll
        for (int i = 0; i < 8; i++) xa[i] = pack2(ln_apply_r(bflo(xa[i]), mean, rden), ln_apply_r(bfhi(xa[i]), mean, rden));
        if (tid == 0) TRACE(14);
        float acc[4][4] = {};
        const int row = (lane & 7) + (lane & 8), ch = (warp & 1) * 4 + (lane >> 4);
        const uint32_t a0 = SB + OFF_CKV + 14 * UNIT + (warp >> 1) * 2048 + row * 128;
#pragma unroll
        for (int s = 0; s < 4; s++) {
            if ((s & 1) == 0) mbar_wait(BAR(s >> 1), 0);
            uint32_t b0, b1, b2, b3, b4, b5, b6, b7;
            ldsm4t(a0 + s * UNIT + ((ch ^ (row & 7)) << 4), b0, b1, b2, b3);
            ldsm4t(a0 + s * UNIT + (((ch + 2) ^ (row & 7)) << 4), b4, b5, b6, b7);
            mma16816(acc[0], xa[2 * s], 0, xa[2 * s + 1], 0, b0, b1);
            mma16816(acc[1], xa[2 * s], 0, xa[2 * s + 1], 0, b2, b3);
            mma16816(acc[2], xa[2 * s], 0, xa[2 * s + 1], 0, b4, b5);
            mma16816(acc[3], xa[2 * s], 0, xa[2 * s + 1], 0, b6, b7);
        }
        const float v0 = (g & 2) ? ((g & 1) ? acc[3][0] : acc[2][0]) : ((g & 1) ? acc[1][0] : acc[0][0]);
        const float v1 = (g & 2) ? ((g & 1) ? acc[3][1] : acc[2][1]) : ((g & 1) ? acc[1][1] : acc[0][1]);
        if (lane < 16) mb_put2f(mb + o1, v0, v1);
        __syncwarp();
        if (lane == 0) mbar_arrive(BAR(G_P1));
    }
    asm volatile("bar.arrive 13, 384;" ::: "memory");
    if (tid == 0) TRACE(1);
    mb_clear2(o3); mb_clear2(o3 + 1024); mb_clear2(o3 + 524288); mb_clear2(o3 + 524288 + 1024);
    if (a4) mb_clear2(o4);
    if (am) { mb_clear2(om); mb_clear2(om + 8 * NC_MAX * 32); }
    if (full) {
        if (lane < 4) mb_clear2(o5);
        if (a6) mb_clear2(o6);
    }
    bar_sync(7, 384);
    if (tid == 0) TRACE(2);
    {
        const int row = (lane & 7) + (lane & 8), cs = lane >> 4;
        const float sc = 0.0625f * 1.4426950408889634f;
        {
            const uint32_t qs = SB + OFF_QST + ((ua >> 6) != hA ? 512 : 0) + t * 16;
            uint4 q[8];
#pragma unroll
            for (int s2 = 0; s2 < 8; s2++) q[s2] = lds128(qs + s2 * 64);
            mbar_wait(BAR(g_uk + (warp >> 1)), 0);
            float c[4][4] = {};
            const uint32_t a0 = SB + OFF_WA + warp * UNIT + row * 128;
#pragma unroll
            for (int s2 = 0; s2 < 8; s2++) {
                uint32_t r0, r1, r2, r3, r4, r5, r6, r7;
                ldsm4(a0 + (s2 >> 1) * 2048 + ((((s2 & 1) * 4 + cs) ^ (row & 7)) << 4), r0, r1, r2, r3);
                ldsm4(a0 + (s2 >> 1) * 2048 + ((((s2 & 1) * 4 + 2 + cs) ^ (row & 7)) << 4), r4, r5, r6, r7);
                mma16816(c[(s2 & 1) * 2], r0, r1, r2, r3, q[s2].x, q[s2].y);
                mma16816(c[(s2 & 1) * 2 + 1], r4, r5, r6, r7, q[s2].z, q[s2].w);
            }
            const float lo = ((c[0][0] + c[1][0]) + (c[2][0] + c[3][0])) * sc, hi = ((c[0][2] + c[1][2]) + (c[2][2] + c[3][2])) * sc;
            const float lo2 = __shfl_down_sync(~0u, lo, 4), hi2 = __shfl_down_sync(~0u, hi, 4);
            if ((lane & 7) == 0) mb_put2(mb + o2a, pack2(lo, lo2), pack2(hi, hi2));
        }
        if (nu > 8 && warp == 0) {
            const uint32_t qs = SB + OFF_QST + ((ub >> 6) != hA ? 512 : 0) + t * 16;
            uint4 q[8];
#pragma unroll
            for (int s2 = 0; s2 < 8; s2++) q[s2] = lds128(qs + s2 * 64);
            mbar_wait(BAR(g_uk + 4), 0);
            float c[4][4] = {};
            const uint32_t a0 = SB + OFF_WA + 8 * UNIT + row * 128;
#pragma unroll
            for (int s2 = 0; s2 < 8; s2++) {
                uint32_t r0, r1, r2, r3, r4, r5, r6, r7;
                ldsm4(a0 + (s2 >> 1) * 2048 + ((((s2 & 1) * 4 + cs) ^ (row & 7)) << 4), r0, r1, r2, r3);
                ldsm4(a0 + (s2 >> 1) * 2048 + ((((s2 & 1) * 4 + 2 + cs) ^ (row & 7)) << 4), r4, r5, r6, r7);
                mma16816(c[(s2 & 1) * 2], r0, r1, r2, r3, q[s2].x, q[s2].y);
                mma16816(c[(s2 & 1) * 2 + 1], r4, r5, r6, r7, q[s2].z, q[s2].w);
            }
            const float lo = ((c[0][0] + c[1][0]) + (c[2][0] + c[3][0])) * sc, hi = ((c[0][2] + c[1][2]) + (c[2][2] + c[3][2])) * sc;
            const float lo2 = __shfl_down_sync(~0u, lo, 4), hi2 = __shfl_down_sync(~0u, hi, 4);
            if ((lane & 7) == 0) mb_put2(mb + o2b, pack2(lo, lo2), pack2(hi, hi2));
        }
    }
    if (tid == 0) TRACE(3);
    asm volatile("bar.arrive 6, 384;" ::: "memory");
    asm volatile("barrier.cluster.wait.acquire.aligned;" ::: "memory");
    {
        float acc[4][4] = {};
        float mr0 = -INFINITY, mr1 = -INFINITY, tl[4] = {};
        const int prow = (lane & 7) + (lane & 8), pch = (warp & 1) * 4 + (lane >> 4);
        const uint32_t p_src0 = SB + OFF_CKV + (warp >> 1) * 2048 + prow * 128 + ((pch ^ (prow & 7)) << 4);
        const uint32_t p_src1 = SB + OFF_CKV + (warp >> 1) * 2048 + prow * 128 + (((pch + 2) ^ (prow & 7)) << 4);
        const uint32_t one = 0x3f803f80u;
#pragma unroll 1
        for (int b = 0, pb = 0, pph = 0; b < nb; b++) {
            const bool two = 2 * b + 1 < nk;
            const uint32_t pbase = SB + p_off(pb);
            mbar_wait(BAR(B_P0 + pb), pph);
            if (tid == 0) TRACE(21 + b);
            uint32_t b0[8], b1[8];
            const float mb0 = __uint_as_float(lds32(pbase + 1024 + g * 4));
            const float mb1 = __uint_as_float(lds32(pbase + 1024 + 32 + g * 4));
            const uint4 p0 = lds128(pbase + lane * 16);
            ldsm4t(p_src0 + 2 * b * UNIT, b0[0], b0[1], b0[2], b0[3]);
            ldsm4t(p_src1 + 2 * b * UNIT, b0[4], b0[5], b0[6], b0[7]);
            uint4 p1;
            if (two) {
                p1 = lds128(pbase + 512 + lane * 16);
                ldsm4t(p_src0 + (2 * b + 1) * UNIT, b1[0], b1[1], b1[2], b1[3]);
                ldsm4t(p_src1 + (2 * b + 1) * UNIT, b1[4], b1[5], b1[6], b1[7]);
            }
            if (__any_sync(~0u, mb0 != mr0 || mb1 != mr1)) {
                const float al0 = ex2(mr0 - mb0), al1 = ex2(mr1 - mb1);
                mr0 = mb0; mr1 = mb1;
#pragma unroll
                for (int i = 0; i < 4; i++) { acc[i][0] *= al0; acc[i][1] *= al0; acc[i][2] *= al1; acc[i][3] *= al1; }
                tl[0] *= al0; tl[2] *= al1;
            }
#pragma unroll
            for (int i = 0; i < 4; i++) mma16816(acc[i], p0.x, p0.y, p0.z, p0.w, b0[2 * i], b0[2 * i + 1]);
            mma16816(tl, p0.x, p0.y, p0.z, p0.w, one, one);
            if (two) {
#pragma unroll
                for (int i = 0; i < 4; i++) mma16816(acc[i], p1.x, p1.y, p1.z, p1.w, b1[2 * i], b1[2 * i + 1]);
                mma16816(tl, p1.x, p1.y, p1.z, p1.w, one, one);
            }
            if (tid == 0 && b + RP < nb) mbar_expect(BAR(B_P0 + pb), (2 * (b + RP) + 1 < nk) ? 1088 : 576);
            __syncwarp();
            if (lane == 0) red_add_rel(SB + OFF_PVC + b * 4, 1);
            if (++pb == RP) { pb = 0; pph ^= 1; }
        }
        if (am) {
            mb_put2f(mb + om, mr0, tl[0]);
            mb_put2f(mb + om + 8 * NC_MAX * 32, mr1, tl[2]);
        }
        mb_put2(mb + o3, pack2(acc[0][0], acc[0][1]), pack2(acc[1][0], acc[1][1]));
        mb_put2(mb + o3 + 1024, pack2(acc[2][0], acc[2][1]), pack2(acc[3][0], acc[3][1]));
        mb_put2(mb + o3 + 524288, pack2(acc[0][2], acc[0][3]), pack2(acc[1][2], acc[1][3]));
        mb_put2(mb + o3 + 524288 + 1024, pack2(acc[2][2], acc[2][3]), pack2(acc[3][2], acc[3][3]));
    }
    if (tid == 0) TRACE(5);
    {
        const uint32_t tpub = clock();
        const unsigned char* psrc = mb + MB3 + ua * 1024 + lane * 16;
        const int pn = (16 + (lane >> 1) < NC) ? 2 : 1;
        const unsigned char* msrc = mb + MBM + ((ua >> 6) * NC_MAX + lane) * 32;
        uint32_t mj = 0xff800000u;
        bar_sync(5, 320);
        uint32_t wb[9][8];
        const int p = (lane & 7) + (lane & 8);
        const int prow = ((p >> 1) & 1) * 8 + (p >> 2) * 2 + (p & 1), pch = (warp & 1) * 4 + (lane >> 4);
        const uint32_t src0 = SB + OFF_WA + (warp >> 1) * 2048 + prow * 128 + ((pch ^ (prow & 7)) << 4);
        const uint32_t src1 = SB + OFF_WA + (warp >> 1) * 2048 + prow * 128 + (((pch + 2) ^ (prow & 7)) << 4);
        uint4 pv[2];
#pragma unroll
        for (int ul = 0; ul < 9; ul++) {
            const uint32_t uo = (ul < 8 || nu > 8) ? ul * UNIT : 0;
            if ((ul & 1) == 0 && (ul < 8 || nu > 8)) mbar_wait(BAR(g_uv + (ul >> 1)), 0);
            ldsm4t(src0 + uo, wb[ul][0], wb[ul][1], wb[ul][2], wb[ul][3]);
            ldsm4t(src1 + uo, wb[ul][4], wb[ul][5], wb[ul][6], wb[ul][7]);
        }
        while (clock() - tpub < ((P.dly >> 10) & 31) * 64) {}
        mb_first<2, 512>(psrc, pn, pv);
        if (lane < NC) mj = mb_ld1(msrc);
        if (tid == 0) TRACE(18);
        const int nA = (hA + 1) * 64 - u0;
        combine_unit(SB, psrc, msrc, pn, lane < NC, pv, mj, warp, lane);
        bar_sync(3, 288);
        if (tid == 0) TRACE(6);
        float acc[2][4][4] = {};
#pragma unroll
        for (int ul = 0; ul < 9; ul++) {
            const uint4 a = lds128((ul < nA) == (g < 4) ? SB + OFF_AFR + ul * 64 + t * 16 : SB + OFF_PVC + 48);
#pragma unroll
            for (int i = 0; i < 4; i++) mma16816(acc[ul & 1][i], a.x, a.y, a.z, a.w, wb[ul][2 * i], wb[ul][2 * i + 1]);
        }
        float v0, v1;
        {
            const int i = g & 3;
            float e[4][2];
#pragma unroll
            for (int k = 0; k < 4; k++) {
                e[k][0] = (acc[0][k][0] + acc[0][k][2]) + (acc[1][k][0] + acc[1][k][2]);
                e[k][1] = (acc[0][k][1] + acc[0][k][3]) + (acc[1][k][1] + acc[1][k][3]);
            }
            v0 = (i & 2) ? ((i & 1) ? e[3][0] : e[2][0]) : ((i & 1) ? e[1][0] : e[0][0]);
            v1 = (i & 2) ? ((i & 1) ? e[3][1] : e[2][1]) : ((i & 1) ? e[1][1] : e[0][1]);
        }
        if (a4) mb_put2f(mb + o4, v0, v1);
    }
    if (tid == 0) TRACE(7);
    if (!full) return;
    asm volatile("bar.arrive 10, 320;" ::: "memory");

    {
        mbar_wait(BAR(g_wo), 0);
        mbar_wait(BAR(g_wo + 1), 0);
        uint32_t b[8][4];
        const uint32_t src = SB + OFF_CKV + lane * 128 + ((warp ^ (lane & 7)) << 4);
#pragma unroll
        for (int s2 = 0; s2 < 8; s2++) ldsm4t(src + s2 * 4096, b[s2][0], b[s2][1], b[s2][2], b[s2][3]);
        bar_sync(8, 320);
        if (tid == 0) TRACE(8);
        float c[4][4] = {};
#pragma unroll
        for (int s2 = 0; s2 < 8; s2++) {
            const uint4 a = lds128(SB + OFF_CTX + s2 * 64 + t * 16);
            mma16816(c[(s2 & 1) * 2], a.x, 0, a.y, 0, b[s2][0], b[s2][1]);
            mma16816(c[(s2 & 1) * 2 + 1], a.z, 0, a.w, 0, b[s2][2], b[s2][3]);
        }
        if (lane < 4) mb_put2f(mb + o5, (c[0][0] + c[1][0]) + (c[2][0] + c[3][0]), (c[0][1] + c[1][1]) + (c[2][1] + c[3][1]));
    }
    asm volatile("bar.arrive 11, 288;" ::: "memory");
    if (tid == 0) TRACE(9);

    {
        mbar_wait(BAR(g_gu), 0);
        mbar_wait(BAR(g_gu + 1), 0);
        uint32_t b[7][4];
        const uint32_t src = SB + OFF_CKV + 4 * UNIT + lane * 128 + ((warp ^ (lane & 7)) << 4);
#pragma unroll
        for (int s2 = 0; s2 < 7; s2++) ldsm4t(src + s2 * 4096, b[s2][0], b[s2][1], b[s2][2], b[s2][3]);
        const uint32_t gdst = mapa(SB + OFF_GU + r * 512 + (warp * 4 + t) * 16, g & 3), gbar = mapa(BAR(B_GU), g & 3);
        mbar_wait(BAR(B_H), 0);
        if (tid == 0) TRACE(10);
        float c[4][4] = {};
        const uint32_t one = 0x3f803f80u;
#pragma unroll
        for (int s2 = 0; s2 < 7; s2++) {
            const uint4 a = lds128(SB + OFF_H + (r >> 1) * 448 + s2 * 64 + t * 16);
            mma16816(c[(s2 & 1) * 2], a.x, one, a.y, one, b[s2][0], b[s2][1]);
            mma16816(c[(s2 & 1) * 2 + 1], a.z, one, a.w, one, b[s2][2], b[s2][3]);
        }
        if (g < 4)
            st_async_v4(gdst, __float_as_uint((c[0][0] + c[1][0]) + (c[2][0] + c[3][0])),
                        __float_as_uint((c[0][1] + c[1][1]) + (c[2][1] + c[3][1])), __float_as_uint((c[0][2] + c[1][2]) + (c[2][2] + c[3][2])),
                        __float_as_uint((c[0][3] + c[1][3]) + (c[2][3] + c[3][3])), gbar);
    }
    {
        mbar_wait(BAR(g_wd), 0);
        uint32_t b[4][4];
        const uint32_t src = SB + OFF_CKV + 8 * UNIT + lane * 128 + ((warp ^ (lane & 7)) << 4);
        ldsm4t(src, b[0][0], b[0][1], b[0][2], b[0][3]);
        ldsm4t(src + 4096, b[1][0], b[1][1], b[1][2], b[1][3]);
        ldsm4t(src + UNIT, b[2][0], b[2][1], b[2][2], b[2][3]);
        ldsm4t(src + UNIT + 4096, b[3][0], b[3][1], b[3][2], b[3][3]);
        mbar_wait(BAR(B_GU), 0);
        if (tid == 0) TRACE(11);
        const uint32_t ga = SB + OFF_GU + (((g & 3) * 2 + (g >> 2)) * 4 + t) * 16;
        const uint4 p0 = lds128(ga), p1 = lds128(ga + 512), p2 = lds128(ga + 1024), p3 = lds128(ga + 1536);
        const float mean = __uint_as_float(lds32(SB + OFF_MISC + 8)), inv = __uint_as_float(lds32(SB + OFF_MISC + 12));
        const float g0 = bf16r(((__uint_as_float(p0.x) + __uint_as_float(p2.x)) - mean * (__uint_as_float(p0.z) + __uint_as_float(p2.z))) * inv);
        const float g1 = bf16r(((__uint_as_float(p0.y) + __uint_as_float(p2.y)) - mean * (__uint_as_float(p0.w) + __uint_as_float(p2.w))) * inv);
        const float u0v = bf16r(((__uint_as_float(p1.x) + __uint_as_float(p3.x)) - mean * (__uint_as_float(p1.z) + __uint_as_float(p3.z))) * inv);
        const float u1v = bf16r(((__uint_as_float(p1.y) + __uint_as_float(p3.y)) - mean * (__uint_as_float(p1.w) + __uint_as_float(p3.w))) * inv);
        const float s0 = bf16r(__fdividef(1.f, 1.f + __expf(-g0))), s1 = bf16r(__fdividef(1.f, 1.f + __expf(-g1)));
        const uint32_t hw = pack2(s0 * u0v, s1 * u1v);
        uint32_t a[8];
#pragma unroll
        for (int k = 0; k < 8; k++) a[k] = __shfl_sync(~0u, hw, k * 4 + t);
        float c0[4] = {}, c1[4] = {}, c2[4] = {}, c3[4] = {};
        mma16816(c0, a[0], 0, a[4], 0, b[0][0], b[0][1]);
        mma16816(c1, a[0], 0, a[4], 0, b[2][0], b[2][1]);
        mma16816(c2, a[1], 0, a[5], 0, b[0][2], b[0][3]);
        mma16816(c3, a[1], 0, a[5], 0, b[2][2], b[2][3]);
        mma16816(c0, a[2], 0, a[6], 0, b[1][0], b[1][1]);
        mma16816(c1, a[2], 0, a[6], 0, b[3][0], b[3][1]);
        mma16816(c2, a[3], 0, a[7], 0, b[1][2], b[1][3]);
        mma16816(c3, a[3], 0, a[7], 0, b[3][2], b[3][3]);
        if (a6) mb_put2f(mb + o6, (g & 1) ? c1[0] + c3[0] : c0[0] + c2[0], (g & 1) ? c1[1] + c3[1] : c0[1] + c2[1]);
    }
    asm volatile("bar.arrive 12, 288;" ::: "memory");
    if (tid == 0) TRACE(12);
}

__device__ float f_q[4096], f_qa[16 * 1024], f_s[16 * 8192], f_cc[64 * 16 * 1024], f_ctx[4096], f_h[448], f_hh[1792];

__device__ __forceinline__ void block_ln(const float* v  , float* o  ) {
    float a[14];
    const int lane = threadIdx.x & 31;
#pragma unroll
    for (int i = 0; i < 14; i++) a[i] = v[lane + 32 * i];
    float mb, den;
    ln_stats(a, mb, den);
    for (int i = threadIdx.x; i < 448; i += blockDim.x) o[i] = bf16r(ln_apply(v[i], mb, den));
    __syncthreads();
}
__global__ void fb_q(const __nv_bfloat16* x, const __nv_bfloat16* wq) {
    __shared__ float xs[448], xn[448];
    for (int i = threadIdx.x; i < 448; i += blockDim.x) xs[i] = __bfloat162float(x[i]);
    __syncthreads();
    block_ln(xs, xn);
    const int c = blockIdx.x * blockDim.x + threadIdx.x;
    float a = 0.f;
    for (int m = 0; m < 448; m++) a += xn[m] * __bfloat162float(wq[(size_t)m * 4096 + c]);
    f_q[c] = bf16r(a);
}
__global__ void fb_qabs(const __nv_bfloat16* wuk) {
    const int row = blockIdx.x * 8 + (threadIdx.x >> 5), lane = threadIdx.x & 31;
    const int h = row & 15, c = row >> 4;
    float a = 0.f;
    for (int d = lane; d < 256; d += 32) a += f_q[h * 256 + d] * __bfloat162float(wuk[(size_t)row * 256 + d]);
    for (int o = 16; o; o >>= 1) a += __shfl_xor_sync(~0u, a, o);
    if (lane == 0) f_qa[h * 1024 + c] = a * 0.0625f;
}
__global__ void fb_scores(const __nv_bfloat16* ckv) {
    const int k = blockIdx.x * 8 + (threadIdx.x >> 5), lane = threadIdx.x & 31;
    float a[16] = {};
    for (int c = lane; c < 1024; c += 32) {
        const float v = __bfloat162float(ckv[(size_t)k * 1024 + c]);
#pragma unroll
        for (int h = 0; h < 16; h++) a[h] += v * f_qa[h * 1024 + c];
    }
#pragma unroll
    for (int h = 0; h < 16; h++) {
        for (int o = 16; o; o >>= 1) a[h] += __shfl_xor_sync(~0u, a[h], o);
        if (lane == 0) f_s[h * 8192 + k] = a[h];
    }
}
__global__ void fb_softmax() {
    __shared__ float red[32];
    float* s = f_s + blockIdx.x * 8192;
    float m = -INFINITY;
    for (int i = threadIdx.x; i < 8192; i += blockDim.x) m = fmaxf(m, s[i]);
    for (int o = 16; o; o >>= 1) m = fmaxf(m, __shfl_xor_sync(~0u, m, o));
    if ((threadIdx.x & 31) == 0) red[threadIdx.x >> 5] = m;
    __syncthreads();
    m = red[0];
    for (int i = 1; i < (int)(blockDim.x >> 5); i++) m = fmaxf(m, red[i]);
    __syncthreads();
    float l = 0.f;
    for (int i = threadIdx.x; i < 8192; i += blockDim.x) { const float e = __expf(s[i] - m); s[i] = e; l += e; }
    for (int o = 16; o; o >>= 1) l += __shfl_xor_sync(~0u, l, o);
    if ((threadIdx.x & 31) == 0) red[threadIdx.x >> 5] = l;
    __syncthreads();
    l = 0.f;
    for (int i = 0; i < (int)(blockDim.x >> 5); i++) l += red[i];
    const float inv = 1.f / l;
    for (int i = threadIdx.x; i < 8192; i += blockDim.x) s[i] *= inv;
}
__global__ void fb_pv(const __nv_bfloat16* ckv) {
    const int c = blockIdx.y * 256 + threadIdx.x, kb = blockIdx.x * 128;
    float a[16] = {};
    for (int k = kb; k < kb + 128; k++) {
        const float v = __bfloat162float(ckv[(size_t)k * 1024 + c]);
#pragma unroll
        for (int h = 0; h < 16; h++) a[h] += v * f_s[h * 8192 + k];
    }
#pragma unroll
    for (int h = 0; h < 16; h++) f_cc[(blockIdx.x * 16 + h) * 1024 + c] = a[h];
}
__global__ void fb_ctx(const __nv_bfloat16* wuv) {
    __shared__ float cc[1024];
    const int h = blockIdx.x;
    for (int c = threadIdx.x; c < 1024; c += 256) {
        float a = 0.f;
        for (int i = 0; i < 64; i++) a += f_cc[(i * 16 + h) * 1024 + c];
        cc[c] = a;
    }
    __syncthreads();
    float a = 0.f;
    for (int c = 0; c < 1024; c++) a += cc[c] * __bfloat162float(wuv[(size_t)c * 4096 + h * 256 + threadIdx.x]);
    f_ctx[h * 256 + threadIdx.x] = bf16r(a);
}
__global__ void fb_o(const __nv_bfloat16* x, const __nv_bfloat16* wo) {
    __shared__ float red[8][32];
    const int m = blockIdx.x * 32 + (threadIdx.x & 31), p = threadIdx.x >> 5;
    float a = 0.f;
    for (int i = p * 512; i < p * 512 + 512; i++) a += f_ctx[i] * __bfloat162float(wo[(size_t)i * 448 + m]);
    red[p][threadIdx.x & 31] = a;
    __syncthreads();
    if (p == 0) {
        for (int i = 1; i < 8; i++) a += red[i][threadIdx.x];
        f_h[m] = bf16r(__bfloat162float(x[m]) + bf16r(a));
    }
}
__global__ void fb_gu(const __nv_bfloat16* wg, const __nv_bfloat16* wu) {
    __shared__ float hs[448], hn[448];
    for (int i = threadIdx.x; i < 448; i += blockDim.x) hs[i] = f_h[i];
    __syncthreads();
    block_ln(hs, hn);
    const int f = blockIdx.x * 64 + threadIdx.x;
    float a = 0.f, b = 0.f;
    for (int m = 0; m < 448; m++) {
        a += hn[m] * __bfloat162float(wg[(size_t)m * 1792 + f]);
        b += hn[m] * __bfloat162float(wu[(size_t)m * 1792 + f]);
    }
    f_hh[f] = bf16r(bf16r(1.f / (1.f + __expf(-bf16r(a)))) * bf16r(b));
}
__global__ void fb_down(const __nv_bfloat16* wd, __nv_bfloat16* out) {
    __shared__ float red[8][32];
    const int m = blockIdx.x * 32 + (threadIdx.x & 31), p = threadIdx.x >> 5;
    float a = 0.f;
    for (int i = p * 224; i < p * 224 + 224; i++) a += f_hh[i] * __bfloat162float(wd[(size_t)i * 448 + m]);
    red[p][threadIdx.x & 31] = a;
    __syncthreads();
    if (p == 0) {
        for (int i = 1; i < 8; i++) a += red[i][threadIdx.x];
        out[m] = __float2bfloat16_rn(f_h[m] + bf16r(a));
    }
}

typedef CUresult (*EncodeFn)(CUtensorMap*, CUtensorMapDataType, cuuint32_t, void*, const cuuint64_t*, const cuuint64_t*,
                             const cuuint32_t*, const cuuint32_t*, CUtensorMapInterleave, CUtensorMapSwizzle,
                             CUtensorMapL2promotion, CUtensorMapFloatOOBfill);

bool encode3(EncodeFn enc, CUtensorMap* m, const void* p, uint64_t rows, uint64_t rowbytes) {
    cuuint64_t dim[3] = {64, rows, rowbytes / 128};
    cuuint64_t str[2] = {rowbytes, 128};
    cuuint32_t box[3] = {64, 16, 4}, es[3] = {1, 1, 1};
    return enc(m, CU_TENSOR_MAP_DATA_TYPE_BFLOAT16, 3, const_cast<void*>(p), dim, str, box, es, CU_TENSOR_MAP_INTERLEAVE_NONE,
               CU_TENSOR_MAP_SWIZZLE_128B, CU_TENSOR_MAP_L2_PROMOTION_NONE, CU_TENSOR_MAP_FLOAT_OOB_FILL_NONE) == CUDA_SUCCESS;
}
bool encode2(EncodeFn enc, CUtensorMap* m, const void* p, uint64_t rows, uint64_t cols, uint32_t boxrows) {
    cuuint64_t dim[2] = {cols, rows};
    cuuint64_t str[1] = {cols * 2};
    cuuint32_t box[2] = {64, boxrows}, es[2] = {1, 1};
    return enc(m, CU_TENSOR_MAP_DATA_TYPE_BFLOAT16, 2, const_cast<void*>(p), dim, str, box, es, CU_TENSOR_MAP_INTERLEAVE_NONE,
               CU_TENSOR_MAP_SWIZZLE_128B, CU_TENSOR_MAP_L2_PROMOTION_NONE, CU_TENSOR_MAP_FLOAT_OOB_FILL_NONE) == CUDA_SUCCESS;
}

int g_force_fallback = 0;
int g_force_nc = 0;
int g_window = 0x392333;
unsigned g_dly = (24u << 10) | (8u << 15);

}

extern "C" void kernel_launch(void* const* d_in, const int* in_sizes, int n_in, void* d_out, int out_size) {
    const __nv_bfloat16* x = (const __nv_bfloat16*)d_in[0];
    const __nv_bfloat16* ckv = (const __nv_bfloat16*)d_in[1];
    const __nv_bfloat16* wq = (const __nv_bfloat16*)d_in[2];
    const __nv_bfloat16* wuk = (const __nv_bfloat16*)d_in[3];
    const __nv_bfloat16* wuv = (const __nv_bfloat16*)d_in[4];
    const __nv_bfloat16* wo = (const __nv_bfloat16*)d_in[5];
    const __nv_bfloat16* wg = (const __nv_bfloat16*)d_in[7];
    const __nv_bfloat16* wu = (const __nv_bfloat16*)d_in[8];
    const __nv_bfloat16* wd = (const __nv_bfloat16*)d_in[9];
    __nv_bfloat16* out = (__nv_bfloat16*)d_out;
    cudaStream_t st = cudaStreamPerThread;

    static int s_init = 0, s_nc = 0;
    static EncodeFn s_enc = nullptr;
    cudaLaunchConfig_t cfg = {};
    cudaLaunchAttribute at[1];
    at[0].id = cudaLaunchAttributeClusterDimension;
    at[0].val.clusterDim.x = 4; at[0].val.clusterDim.y = 1; at[0].val.clusterDim.z = 1;
    cfg.blockDim = dim3(NTHR); cfg.dynamicSmemBytes = SMEM_BYTES + 128; cfg.stream = st; cfg.attrs = at; cfg.numAttrs = 1;
    if (!s_init) {
        s_init = 1;
        void* fn = nullptr;
        cudaDriverEntryPointQueryResult qr;
        if (cudaGetDriverEntryPoint("cuTensorMapEncodeTiled", &fn, cudaEnableDefault, &qr) == cudaSuccess &&
            qr == cudaDriverEntryPointSuccess)
            s_enc = (EncodeFn)fn;
        int nc = 0;
        cfg.gridDim = dim3(4 * NC_MAX);
        if (cudaFuncSetAttribute(fused_kernel, cudaFuncAttributeMaxDynamicSharedMemorySize, SMEM_BYTES + 128) == cudaSuccess &&
            cudaOccupancyMaxActiveClusters(&nc, fused_kernel, &cfg) == cudaSuccess)
            s_nc = nc > NC_MAX ? NC_MAX : nc;
        (void)cudaGetLastError();
    }
    if (g_force_nc && g_force_nc < s_nc) s_nc = g_force_nc;
    Params P;
    bool ok = s_enc != nullptr && s_nc >= NC_MIN && !g_force_fallback;
    ok = ok && encode3(s_enc, &P.wq, wq, 448, 8192) && encode3(s_enc, &P.wuk, wuk, 1024, 8192) &&
         encode3(s_enc, &P.ckv, ckv, 8192, 2048) && encode3(s_enc, &P.wuv, wuv, 1024, 8192) &&
         encode2(s_enc, &P.wo, wo, 4096, 448, 64) && encode2(s_enc, &P.wg, wg, 448, 1792, 112) &&
         encode2(s_enc, &P.wu, wu, 448, 1792, 112) && encode2(s_enc, &P.wd, wd, 1792, 448, 64);
    if (ok) {
        P.x = x; P.out = out; P.NC = s_nc; P.W = g_window; P.dly = g_dly;
        const int N = 4 * s_nc;
        int ustart[4 * NC_MAX + 1], kstart[NC_MAX + 1];
        {
            const int kbase = 512 / s_nc, kext = 512 - kbase * s_nc;
            kstart[0] = 0;
            for (int jj = 0; jj < s_nc; jj++) kstart[jj + 1] = kstart[jj] + kbase + (jj >= s_nc - kext ? 1 : 0);
            int cap = 0;
            for (int c = 0; c < N; c++) cap += (kstart[(c >> 2) + 1] - kstart[c >> 2] > 17) ? 8 : 9;
            const bool deep = cap >= 1024;
            P.RS = deep ? 5 : 3;
            int nine = 0;
            for (int c = 0; c < N; c++) nine += (!deep || kstart[(c >> 2) + 1] - kstart[c >> 2] <= 17) ? 1 : 0;
            const int uext = 1024 - 8 * N;
            ustart[0] = 0;
            for (int c = 0, i = 0; c < N; c++) {
                int extra = 0;
                if (!deep || kstart[(c >> 2) + 1] - kstart[c >> 2] <= 17) { extra = (i + 1) * uext / nine - i * uext / nine; i++; }
                ustart[c + 1] = ustart[c] + 8 + extra;
            }
        }
        auto owner = [&](int u) { int c = 0; while (ustart[c + 1] <= u) c++; return c; };
        for (int c = 0; c < 4 * NC_MAX; c++) {
            if (c >= N) { P.tab[c] = make_uint2(0, 0); continue; }
            const int jj = c >> 2, u0 = ustart[c], nu = ustart[c + 1] - u0;
            const int k0 = kstart[jj], nk = kstart[jj + 1] - k0;
            const int h7 = (c / 7) & 15, mb7 = c % 7, hA = u0 >> 6, hB = (u0 + nu - 1) >> 6;
            const int ns = owner(h7 * 64 + 63) - owner(h7 * 64) + 1;
            P.tab[c].x = u0 | (nu << 10) | (k0 << 14) | (nk << 23);
            P.tab[c].y = h7 | (mb7 << 4) | ((c - owner(hA * 64)) << 8) | ((c - owner(hB * 64)) << 12) | (ns << 16);
        }
        cfg.gridDim = dim3(4 * s_nc);
        cudaLaunchKernelEx(&cfg, fused_kernel, P);
        return;
    }
    fb_q<<<16, 256, 0, st>>>(x, wq);
    fb_qabs<<<2048, 256, 0, st>>>(wuk);
    fb_scores<<<1024, 256, 0, st>>>(ckv);
    fb_softmax<<<16, 1024, 0, st>>>();
    fb_pv<<<dim3(64, 4), 256, 0, st>>>(ckv);
    fb_ctx<<<16, 256, 0, st>>>(wuv);
    fb_o<<<14, 256, 0, st>>>(x, wo);
    fb_gu<<<28, 64, 0, st>>>(wg, wu);
    fb_down<<<14, 256, 0, st>>>(wd, out);
}
```

```cpp
#include <cuda_runtime.h>
#include <cuda_bf16.h>
#include <cuda.h>
#include <stdint.h>
#include <limits.h>

namespace {

constexpr int NC_MAX = 32, NC_MIN = 29;
constexpr int NTHR = 512;

constexpr uint32_t UNIT = 8192;
constexpr uint32_t OFF_CKV = 0;
constexpr uint32_t OFF_WA = 18 * UNIT;
constexpr uint32_t OFF_X = OFF_WA + 9 * UNIT;
constexpr uint32_t OFF_SLOT = OFF_X;
constexpr uint32_t OFF_PBUF = OFF_X + 3 * 2048;
constexpr uint32_t PSTRIDE = 1088;
constexpr uint32_t OFF_BAR = OFF_PBUF + 4 * PSTRIDE;
constexpr uint32_t OFF_MISC = OFF_BAR + 42 * 8;
constexpr uint32_t OFF_WGT = OFF_CKV + 10 * UNIT;
constexpr uint32_t OFF_REF = OFF_MISC + 16;
constexpr uint32_t OFF_PVC = OFF_REF + 48;
constexpr uint32_t SMEM_BYTES = OFF_PVC + 64;
constexpr uint32_t OFF_QST = OFF_PBUF;
constexpr uint32_t OFF_TILE = OFF_X;
constexpr uint32_t OFF_CTX = OFF_X + 9216;
constexpr uint32_t OFF_AFR = OFF_X + 9728;
constexpr uint32_t OFF_H = OFF_X;
constexpr uint32_t OFF_GU = OFF_X + 1024;
static_assert(OFF_AFR + 576 <= OFF_BAR, "staging overflow");
static_assert(SMEM_BYTES + 128 <= 232448, "smem overflow");

enum { B_S0 = 26, B_P0 = 31, B_H = 37, B_GU = 38, G_P1 = 39, G_QA = 40, NBARS = 41 };

struct __align__(64) Params {
    CUtensorMap wq, wuk, ckv, wuv, wo, wg, wu, wd;
    const __nv_bfloat16* x;
    __nv_bfloat16* out;
    int NC;
    int W;
    unsigned dly;
    int RS;
    uint2 tab[4 * NC_MAX];
};

constexpr uint32_t MB1 = 0;
constexpr uint32_t MB2 = MB1 + 112 * 1024;
constexpr uint32_t MB3 = MB2 + 32768;
constexpr uint32_t MBM = MB3 + 1024 * 1024;
constexpr uint32_t MB4 = MBM + 16384;
constexpr uint32_t MB5 = MB4 + 16 * 12 * 1024;
constexpr uint32_t MB6 = MB5 + 16 * 1792;
constexpr uint32_t MB_SET = (MB6 + 4 * 28 * 28 * 32 + 1023) / 1024 * 1024;
__device__ __align__(1024) unsigned char g_mb[2 * MB_SET];
__device__ unsigned g_epoch;
#define TRACE(i) do {} while (0)

constexpr int SPIN_LIMIT = 1 << 18;
__device__ __forceinline__ void mbar_init(uint32_t b, uint32_t c) {
    asm volatile("mbarrier.init.shared::cta.b64 [%0], %1;" ::"r"(b), "r"(c) : "memory");
}
__device__ __forceinline__ void mbar_expect(uint32_t b, uint32_t bytes) {
    asm volatile("mbarrier.arrive.expect_tx.shared::cta.b64 _, [%0], %1;" ::"r"(b), "r"(bytes) : "memory");
}
__device__ __forceinline__ void mbar_arrive(uint32_t b) {
    asm volatile("mbarrier.arrive.shared::cta.b64 _, [%0];" ::"r"(b) : "memory");
}
__device__ __forceinline__ bool mbar_try(uint32_t b, uint32_t ph) {
    uint32_t ok;
    asm volatile("{.reg .pred p; mbarrier.try_wait.parity.shared::cta.b64 p, [%1], %2; selp.u32 %0,1,0,p;}"
                 : "=r"(ok) : "r"(b), "r"(ph) : "memory");
    return ok;
}
__device__ __forceinline__ void mbar_wait(uint32_t b, uint32_t ph) {
#pragma unroll 1
    for (int i = 0; i < SPIN_LIMIT; i++)
        if (mbar_try(b, ph)) return;
}
__device__ __forceinline__ void tma2p(uint32_t dst, const CUtensorMap* m, int x, int y, uint32_t bar, unsigned long long pol) {
    asm volatile("cp.async.bulk.tensor.2d.shared::cluster.global.mbarrier::complete_tx::bytes.L2::cache_hint [%0], [%1, {%3, %4}], [%2], %5;"
                 ::"r"(dst), "l"(m), "r"(bar), "r"(x), "r"(y), "l"(pol) : "memory");
}
__device__ __forceinline__ void tma3p(uint32_t dst, const CUtensorMap* m, int x, int y, int z, uint32_t bar, unsigned long long pol) {
    asm volatile("cp.async.bulk.tensor.3d.shared::cluster.global.mbarrier::complete_tx::bytes.L2::cache_hint [%0], [%1, {%3, %4, %5}], [%2], %6;"
                 ::"r"(dst), "l"(m), "r"(bar), "r"(x), "r"(y), "r"(z), "l"(pol) : "memory");
}
__device__ __forceinline__ uint32_t mapa(uint32_t a, uint32_t rank) {
    uint32_t r;
    asm("mapa.shared::cluster.u32 %0, %1, %2;" : "=r"(r) : "r"(a), "r"(rank));
    return r;
}
__device__ __forceinline__ void st_async_v4(uint32_t a, uint32_t x, uint32_t y, uint32_t z, uint32_t w, uint32_t bar) {
    asm volatile("st.async.weak.shared::cluster.mbarrier::complete_tx::bytes.v4.b32 [%0], {%1,%2,%3,%4}, [%5];"
                 ::"r"(a), "r"(x), "r"(y), "r"(z), "r"(w), "r"(bar) : "memory");
}
__device__ __forceinline__ void st_async_b32(uint32_t a, uint32_t x, uint32_t bar) {
    asm volatile("st.async.weak.shared::cluster.mbarrier::complete_tx::bytes.b32 [%0], %1, [%2];"
                 ::"r"(a), "r"(x), "r"(bar) : "memory");
}
__device__ __forceinline__ void ldsm4(uint32_t a, uint32_t& r0, uint32_t& r1, uint32_t& r2, uint32_t& r3) {
    asm volatile("ldmatrix.sync.aligned.m8n8.x4.shared.b16 {%0,%1,%2,%3}, [%4];"
                 : "=r"(r0), "=r"(r1), "=r"(r2), "=r"(r3) : "r"(a) : "memory");
}
__device__ __forceinline__ void ldsm4t(uint32_t a, uint32_t& r0, uint32_t& r1, uint32_t& r2, uint32_t& r3) {
    asm volatile("ldmatrix.sync.aligned.m8n8.x4.trans.shared.b16 {%0,%1,%2,%3}, [%4];"
                 : "=r"(r0), "=r"(r1), "=r"(r2), "=r"(r3) : "r"(a) : "memory");
}
__device__ __forceinline__ void mma16816(float (&c)[4], uint32_t a0, uint32_t a1, uint32_t a2, uint32_t a3, uint32_t b0, uint32_t b1) {
    asm("mma.sync.aligned.m16n8k16.row.col.f32.bf16.bf16.f32 {%0,%1,%2,%3}, {%4,%5,%6,%7}, {%8,%9}, {%0,%1,%2,%3};"
                 : "+f"(c[0]), "+f"(c[1]), "+f"(c[2]), "+f"(c[3]) : "r"(a0), "r"(a1), "r"(a2), "r"(a3), "r"(b0), "r"(b1));
}
__device__ __forceinline__ uint4 lds128(uint32_t a) {
    uint4 v;
    asm volatile("ld.shared.v4.u32 {%0,%1,%2,%3}, [%4];" : "=r"(v.x), "=r"(v.y), "=r"(v.z), "=r"(v.w) : "r"(a) : "memory");
    return v;
}
__device__ __forceinline__ uint32_t lds32(uint32_t a) {
    uint32_t v;
    asm volatile("ld.shared.u32 %0, [%1];" : "=r"(v) : "r"(a) : "memory");
    return v;
}
__device__ __forceinline__ uint32_t lds32_vol(uint32_t a) {
    uint32_t v;
    asm volatile("ld.volatile.shared.u32 %0, [%1];" : "=r"(v) : "r"(a) : "memory");
    return v;
}
__device__ __forceinline__ uint4 lds128_vol(uint32_t a) {
    uint4 v;
    asm volatile("ld.volatile.shared.v4.u32 {%0,%1,%2,%3}, [%4];" : "=r"(v.x), "=r"(v.y), "=r"(v.z), "=r"(v.w) : "r"(a) : "memory");
    return v;
}
__device__ __forceinline__ void sts128_vol(uint32_t a, uint4 v) {
    asm volatile("st.volatile.shared.v4.u32 [%0], {%1,%2,%3,%4};" ::"r"(a), "r"(v.x), "r"(v.y), "r"(v.z), "r"(v.w) : "memory");
}
__device__ __forceinline__ void red_add(uint32_t a, uint32_t v) {
    asm volatile("red.relaxed.cta.shared.add.u32 [%0], %1;" ::"r"(a), "r"(v) : "memory");
}
__device__ __forceinline__ void pv_wait(uint32_t pvc, int k) {
#pragma unroll 1
    for (int it = 0; it < SPIN_LIMIT * 8; it++)
        if ((int)lds32_vol(pvc + k * 4) >= 8) return;
}
__device__ __forceinline__ void sts128(uint32_t a, uint4 v) {
    asm volatile("st.shared.v4.u32 [%0], {%1,%2,%3,%4};" ::"r"(a), "r"(v.x), "r"(v.y), "r"(v.z), "r"(v.w) : "memory");
}
__device__ __forceinline__ void sts32(uint32_t a, uint32_t v) {
    asm volatile("st.shared.u32 [%0], %1;" ::"r"(a), "r"(v) : "memory");
}
__device__ __forceinline__ void sts16(uint32_t a, uint16_t v) {
    asm volatile("st.shared.u16 [%0], %1;" ::"r"(a), "h"(v) : "memory");
}
__device__ __forceinline__ void bar_sync(int id, int n) {
    asm volatile("bar.sync %0, %1;" ::"r"(id), "r"(n) : "memory");
}
__device__ __forceinline__ float bf16r(float v) { return __bfloat162float(__float2bfloat16_rn(v)); }
__device__ __forceinline__ uint32_t pack2(float lo, float hi) {
    __nv_bfloat162 t = __floats2bfloat162_rn(lo, hi);
    return *reinterpret_cast<uint32_t*>(&t);
}
__device__ __forceinline__ float bflo(uint32_t w) { return __uint_as_float(w << 16); }
__device__ __forceinline__ float bfhi(uint32_t w) { return __uint_as_float(w & 0xffff0000u); }
__device__ __forceinline__ float ex2(float x) {
    float y;
    asm("ex2.approx.ftz.f32 %0, %1;" : "=f"(y) : "f"(x));
    return y;
}
__device__ __forceinline__ uint32_t ldg_early(const uint32_t* p) {
    uint32_t v;
    asm volatile("ld.global.nc.u32 %0, [%1];" : "=r"(v) : "l"(p));
    return v;
}

__device__ __forceinline__ void mb_st2(unsigned char* p, uint32_t a, uint32_t b) {
    asm volatile("st.relaxed.gpu.global.v2.u32 [%0], {%1,%2};" ::"l"(p), "r"(a), "r"(b) : "memory");
}
__device__ __forceinline__ void mb_put2(unsigned char* p, uint32_t a, uint32_t b) { mb_st2(p, a == 0u ? 0x80000000u : a, b); }
__device__ __forceinline__ void mb_put2f(unsigned char* p, float a, float b) { mb_put2(p, __float_as_uint(a), __float_as_uint(b)); }
__device__ __forceinline__ void mb_clear2(uint32_t off) {
    mb_st2(g_mb + off, 0u, 0u);
    mb_st2(g_mb + MB_SET + off, 0u, 0u);
}
__device__ __forceinline__ uint4 mb_ld4(const unsigned char* p) {
    uint4 v;
    asm volatile("ld.relaxed.gpu.global.v4.u32 {%0,%1,%2,%3}, [%4];" : "=r"(v.x), "=r"(v.y), "=r"(v.z), "=r"(v.w) : "l"(p) : "memory");
    return v;
}
template <int N, int STRIDE>
__device__ __forceinline__ void mb_poll(const unsigned char* p, int n, uint4 (&v)[N]) {
#pragma unroll
    for (int i = 0; i < N; i++) v[i] = i < n ? mb_ld4(p + i * STRIDE) : make_uint4(0, 0, 0, 0);
#pragma unroll 1
    for (int it = 0; it < SPIN_LIMIT; it++) {
        uint32_t m = 0xffffffffu;
#pragma unroll
        for (int i = 0; i < N; i++)
            if (i < n) m = min(m, min(v[i].x, v[i].z));
        if (m != 0u) break;
#pragma unroll
        for (int i = 0; i < N; i++)
            if (i < n && (N > 4 || min(v[i].x, v[i].z) == 0u)) v[i] = mb_ld4(p + i * STRIDE);
    }
}
__device__ __forceinline__ void delay(uint32_t clks) {
    const uint32_t t0 = clock();
    while (clock() - t0 < clks) {}
}

template <int N, int STRIDE>
__device__ __forceinline__ void mb_first(const unsigned char* p, int n, uint4 (&v)[N]) {
#pragma unroll
    for (int i = 0; i < N; i++) v[i] = i < n ? mb_ld4(p + i * STRIDE) : make_uint4(0, 0, 0, 0);
}
__device__ __forceinline__ void ln_stats(const float (&v)[14], float& mb, float& den) {
    float s = 0.f;
#pragma unroll
    for (int i = 0; i < 14; i++) s += v[i];
#pragma unroll
    for (int o = 16; o; o >>= 1) s += __shfl_xor_sync(~0u, s, o);
    const float mean = s * (1.f / 448.f);
    float q = 0.f;
#pragma unroll
    for (int i = 0; i < 14; i++) { const float d = v[i] - mean; q += d * d; }
#pragma unroll
    for (int o = 16; o; o >>= 1) q += __shfl_xor_sync(~0u, q, o);
    mb = bf16r(mean);
    den = bf16r(__fsqrt_rn(bf16r(bf16r(q * (1.f / 448.f)) + 1e-5f)));
}
__device__ __forceinline__ void ln_stats1(const float (&v)[14], float c, float& mb, float& den) {
    float s0 = 0.f, s1 = 0.f, q0 = 0.f, q1 = 0.f;
#pragma unroll
    for (int i = 0; i < 7; i++) {
        const float d0 = v[2 * i] - c, d1 = v[2 * i + 1] - c;
        s0 += d0; s1 += d1; q0 += d0 * d0; q1 += d1 * d1;
    }
    float s = s0 + s1, q = q0 + q1;
#pragma unroll
    for (int o = 16; o; o >>= 1) { s += __shfl_xor_sync(~0u, s, o); q += __shfl_xor_sync(~0u, q, o); }
    const float md = s * (1.f / 448.f);
    mb = bf16r(c + md);
    den = bf16r(__fsqrt_rn(bf16r(bf16r(fmaxf(q * (1.f / 448.f) - md * md, 0.f)) + 1e-5f)));
}
__device__ __forceinline__ float ln_apply(float v, float mb, float den) { return __fdiv_rn(bf16r(v - mb), den); }
__device__ __forceinline__ float ln_apply_r(float v, float mb, float rden) { return bf16r(v - mb) * rden; }

__device__ __forceinline__ uint32_t frag_off(int w) {
    const int s = w >> 3, half = (w >> 2) & 1, t = w & 3;
    return (uint32_t)((((s >> 1) * 4 + t) * 4 + (s & 1) * 2 + half) * 4);
}
__device__ __forceinline__ int f2o(float f) { const int i = __float_as_int(f); return i ^ ((i >> 31) & 0x7fffffff); }
__device__ __forceinline__ float o2f(int i) { return __int_as_float(i ^ ((i >> 31) & 0x7fffffff)); }

__device__ __forceinline__ uint32_t mb_ld1(const unsigned char* p) {
    uint32_t v;
    asm volatile("ld.relaxed.gpu.global.u32 %0, [%1];" : "=r"(v) : "l"(p) : "memory");
    return v;
}
__device__ __forceinline__ void combine_unit(uint32_t SB, const unsigned char* src, const unsigned char* msrc, int n, bool mact,
                                             uint4 (&v)[2], uint32_t mj, int ul, int lane) {
#pragma unroll 1
    for (int it = 0; it < SPIN_LIMIT; it++) {
        uint32_t m = mj;
        if (n > 0) m = min(m, min(v[0].x, v[0].z));
        if (n > 1) m = min(m, min(v[1].x, v[1].z));
        if (m != 0u) break;
        if (n > 0 && min(v[0].x, v[0].z) == 0u) v[0] = mb_ld4(src);
        if (n > 1 && min(v[1].x, v[1].z) == 0u) v[1] = mb_ld4(src + 512);
        if (mj == 0u) mj = mb_ld1(msrc);
    }
    __syncwarp();
    const uint32_t tile = SB + OFF_TILE + ul * 1024, wgt = SB + OFF_WGT + ul * 128;
    sts128(tile + lane * 16, v[0]);
    sts128(tile + 512 + lane * 16, v[1]);
    {
        const float mf = __uint_as_float(mj);
        const float w = ex2(mf - o2f(__reduce_max_sync(~0u, f2o(mf))));
        const int jj = lane & 15;
        const uint32_t d = wgt + ((lane >> 4) * 4 + ((jj & 7) >> 1)) * 16 + (jj >> 3) * 8 + (jj & 1) * 2;
        const __nv_bfloat16 hi = __float2bfloat16_rn(w), lo = __float2bfloat16_rn(w - __bfloat162float(hi));
        sts16(d, *reinterpret_cast<const uint16_t*>(&hi));
        sts16(d + 4, *reinterpret_cast<const uint16_t*>(&lo));
    }
    __syncwarp();
    const int t = lane & 3;
    uint32_t b[8];
    const uint32_t ts = tile + ((lane & 7) + (lane & 8)) * 32 + (lane >> 4) * 16;
    ldsm4t(ts, b[0], b[1], b[2], b[3]);
    ldsm4t(ts + 512, b[4], b[5], b[6], b[7]);
    const uint4 w0 = lds128(wgt + t * 16), w1 = lds128(wgt + 64 + t * 16);
    float c0[4] = {}, c1[4] = {}, c2[4] = {}, c3[4] = {};
    mma16816(c0, w0.x, w0.y, w0.z, w0.w, b[0], b[1]);
    mma16816(c1, w0.x, w0.y, w0.z, w0.w, b[2], b[3]);
    mma16816(c2, w1.x, w1.y, w1.z, w1.w, b[4], b[5]);
    mma16816(c3, w1.x, w1.y, w1.z, w1.w, b[6], b[7]);
    const float v0 = (c0[0] + c0[2]) + (c2[0] + c2[2]), v1 = (c0[1] + c0[3]) + (c2[1] + c2[3]);
    const float v2 = (c1[0] + c1[2]) + (c3[0] + c3[2]), v3 = (c1[1] + c1[3]) + (c3[1] + c3[3]);
    const uint32_t a0 = pack2(v0, v1), a2 = pack2(v2, v3);
    const uint32_t a1 = pack2(v0 - bflo(a0), v1 - bfhi(a0)), a3 = pack2(v2 - bflo(a2), v3 - bfhi(a2));
    if (lane < 4) sts128(SB + OFF_AFR + ul * 64 + t * 16, make_uint4(a0, a1, a2, a3));
}

__global__ void __launch_bounds__(NTHR, 1) fused_kernel(const __grid_constant__ Params P) {
    extern __shared__ __align__(1024) unsigned char smem_raw[];
    const uint32_t SB = (uint32_t)__cvta_generic_to_shared(smem_raw);
    const int tid = threadIdx.x, warp = tid >> 5, lane = tid & 31;
    const int g = lane >> 2, t = lane & 3;
    const int cta = blockIdx.x, j = cta >> 2, r = cta & 3;
    const uint2 tab = P.tab[cta];
    const int u0 = tab.x & 1023, nu = (tab.x >> 10) & 15, k0 = (tab.x >> 14) & 511, nk = (tab.x >> 23) & 31;
    const int h7 = tab.y & 15, mb7 = (tab.y >> 4) & 7;
    const bool full = cta < 112;
    const int nb = (nk + 1) >> 1, nbg = nk >> 1;
    const int g_uk = full ? 2 : 0, g_kv = g_uk + 4, g_uv = g_kv + nbg, g_wo = g_uv + 4, g_gu = g_wo + 2, g_wd = g_gu + 2;
    auto BAR = [&](int i) -> uint32_t { return SB + OFF_BAR + 8 * i; };

    if (warp == 11) {
        const int W1 = P.W & 15, W2 = (P.W >> 4) & 15, W3 = (P.W >> 8) & 15, W4 = (P.W >> 12) & 15, ngroups = full ? g_wd + 1 : g_wo;
        int done = 0;
        unsigned long long pol;
        asm volatile("createpolicy.fractional.L2::evict_first.b64 %0, 1.0;" : "=l"(pol));
        if (lane < 8) asm volatile("prefetch.tensormap [%0];" ::"l"(reinterpret_cast<const char*>(&P) + lane * 128) : "memory");
        if (lane == 0) {
            mbar_init(BAR(0), 1);
            mbar_init(BAR(1), 1);
            mbar_init(BAR(2), 1);
            mbar_init(BAR(3), 1);
            asm volatile("fence.mbarrier_init.release.cluster;" ::: "memory");
        }
        __syncwarp();
#pragma unroll 1
        for (int gi = 0; gi < ngroups; gi++) {
            if (gi == min(W1, 4)) {
                __syncthreads();
                asm volatile("barrier.cluster.arrive.relaxed.aligned;" ::: "memory");
            }
            const CUtensorMap* map;
            uint32_t dst, dstep = UNIT;
            int n = 2, x0 = 0, y0, z0 = -1, x1 = 0, y1, z1 = 0, y2 = 0, z2 = 0, gate = -1, pvgate = 0;
            if (gi < g_uk) {
                map = &P.wq; dst = OFF_CKV + (14 + 2 * gi) * UNIT;
                y0 = mb7 * 64 + gi * 32; y1 = y0 + 16; z0 = z1 = h7 * 4;
            } else if (gi < g_kv || (gi >= g_uv && gi < g_wo)) {
                const bool uv = gi >= g_uv;
                const int i0 = 2 * (gi - (uv ? g_uv : g_uk)), u = u0 + i0;
                if (gi == g_uv) gate = G_QA;
                map = uv ? &P.wuv : &P.wuk; dst = OFF_WA + i0 * UNIT; n = i0 == 6 ? nu - 6 : 2;
                y0 = (u & 63) * 16; z0 = (u >> 6) * 4; y1 = ((u + 1) & 63) * 16; z1 = ((u + 1) >> 6) * 4;
                y2 = ((u + 2) & 63) * 16; z2 = ((u + 2) >> 6) * 4;
            } else if (gi < g_uv) {
                const int b = gi - g_kv;
                if (b == 7 && full) gate = G_P1;
                map = &P.ckv; dst = OFF_CKV + 2 * b * UNIT; n = b == nbg - 1 ? nk - 2 * b : 2;
                y0 = (k0 + 2 * b) * 16; y1 = y0 + 16; y2 = y0 + 32; z0 = z1 = z2 = r * 4;
            } else if (gi < g_gu) {
                const int i = gi - g_wo;
                pvgate = 1;
                map = &P.wo; dst = OFF_CKV + 2 * i * UNIT;
                x0 = x1 = mb7 * 64; y0 = h7 * 256 + i * 128; y1 = y0 + 64;
            } else if (gi < g_wd) {
                const int i = gi - g_gu;
                pvgate = 3;
                map = (r & 1) ? &P.wu : &P.wg; dst = OFF_CKV + 4 * UNIT + i * 14336; n = 1; dstep = 14336;
                x0 = j * 64; y0 = (r >> 1) * 224 + i * 112; y1 = 0;
            } else {
                pvgate = 4;
                map = &P.wd; dst = OFF_CKV + 8 * UNIT;
                x0 = r * 112; x1 = x0 + 64; y0 = y1 = j * 64;
            }
            if (gate >= 0) mbar_wait(BAR(gate), 0);
            if (pvgate) pv_wait(SB + OFF_PVC, pvgate);
            {
                const int W = gi < g_kv ? W1 : gi < g_uv ? W2 : gi < g_wo ? W3 : W4;
#pragma unroll 1
                for (; done <= gi - W; done++) mbar_wait(BAR(done), 0);
            }
            if (lane == 0) {
                const uint32_t bar = BAR(gi);
                mbar_expect(bar, n * dstep);
                if (z0 >= 0) {
                    tma3p(SB + dst, map, 0, y0, z0, bar, pol);
                    tma3p(SB + dst + UNIT, map, 0, y1, z1, bar, pol);
                    if (n > 2) tma3p(SB + dst + 2 * UNIT, map, 0, y2, z2, bar, pol);
                } else {
                    tma2p(SB + dst, map, x0, y0, bar, pol);
                    if (n > 1) tma2p(SB + dst + UNIT, map, x1, y1, bar, pol);
                }
                if (gi == g_kv) TRACE(15);
                if (gi == g_uv) TRACE(19);
                if (gi == g_wo) TRACE(20);
            }
            __syncwarp();
        }
        if (lane == 0) TRACE(31);
        asm volatile("barrier.cluster.wait.acquire.aligned;" ::: "memory");
        return;
    }

    uint32_t epoch, xr[7], xa[8], xw0, xw1;
    {
        const uint32_t* x32 = reinterpret_cast<const uint32_t*>(P.x);
        asm volatile("ld.relaxed.gpu.global.u32 %0, [%1];" : "=r"(epoch) : "l"(&g_epoch) : "memory");
#pragma unroll
        for (int i = 0; i < 7; i++) xr[i] = ldg_early(x32 + lane + 32 * i);
#pragma unroll
        for (int i = 0; i < 8; i++) xa[i] = ldg_early(x32 + mb7 * 32 + (i >> 1) * 8 + (i & 1) * 4 + t);
        xw0 = ldg_early(x32 + r * 56 + 2 * min(lane, 27));
        xw1 = ldg_early(x32 + r * 56 + 2 * min(lane, 27) + 1);
    }
    if (lane == 0) {
#pragma unroll 1
        for (int i = 4 + (warp > 11 ? warp - 1 : warp); i < NBARS; i += 15) mbar_init(BAR(i), i == G_P1 ? 8 : i == G_QA ? 4 : i == B_GU ? 2 : 1);
        if (warp >= 8 && warp < 11) sts128(SB + OFF_REF + (warp - 8) * 16, make_uint4(0, 0, 0, 0));
        if (warp >= 12) sts128(SB + OFF_PVC + (warp - 12) * 16, make_uint4(0, 0, 0, 0));
        asm volatile("fence.mbarrier_init.release.cluster;" ::: "memory");
    }
    __syncthreads();
    asm volatile("barrier.cluster.arrive.relaxed.aligned;" ::: "memory");
    const int NC = P.NC;
    const int hA = u0 >> 6, hB = (u0 + nu - 1) >> 6;
    const int RS = P.RS, RP = RS + 1;
    const uint32_t xoff = nk <= 17 ? OFF_CKV + 17 * UNIT : OFF_WA + 8 * UNIT;
    auto slot_off = [&](int i) -> uint32_t { return i < 3 ? OFF_SLOT + i * 2048 : xoff + (i - 3) * 2048; };
    auto p_off = [&](int i) -> uint32_t { return i < 4 ? OFF_PBUF + i * PSTRIDE : xoff + 4096 + (i - 4) * PSTRIDE; };

    if (warp >= 12) {
        const int nt = warp - 12;
        const uint32_t s_dst = mapa(SB + r * 512 + (nt * 2 + (g >> 2)) * 64 + t * 16, g & 3);
        const uint32_t s_bar = mapa(BAR(B_S0), g & 3);
        const int srow = (nt & 1) * 8 + (lane & 7);
        const uint32_t s_src0 = SB + OFF_CKV + (nt >> 1) * UNIT + srow * 128 + (((lane >> 3) ^ (srow & 7)) << 4);
        const uint32_t s_src1 = SB + OFF_CKV + (nt >> 1) * UNIT + srow * 128 + (((4 + (lane >> 3)) ^ (srow & 7)) << 4);
        unsigned char* const mb = g_mb + (epoch & 1) * MB_SET;
        const int ht = tid - 384;
        bar_sync(13, 384);
        delay((P.dly & 31) * 64);
        if (ht < 64 || hB != hA) {
            const int i = ht & 63, hs = ht >> 6;
            uint4 v[7];
            mb_poll<7, 1024>(mb + MB1 + (hs ? hB : hA) * 7168 + i * 16, 7, v);
            float a0 = 0.f, a1 = 0.f, a2 = 0.f, a3 = 0.f;
#pragma unroll
            for (int k = 0; k < 7; k++) {
                a0 += __uint_as_float(v[k].x); a1 += __uint_as_float(v[k].y);
                a2 += __uint_as_float(v[k].z); a3 += __uint_as_float(v[k].w);
            }
            const uint32_t d = SB + OFF_QST + hs * 512 + frag_off(2 * i);
            sts32(d, pack2(a0, a1));
            sts32(d + 16, pack2(a2, a3));
        }
        asm volatile("bar.arrive 7, 384;" ::: "memory");
        asm volatile("barrier.cluster.wait.acquire.aligned;" ::: "memory");
        {
            bar_sync(6, 384);
            delay(((P.dly >> 5) & 31) * 64);
            uint4 v[4];
            mb_poll<4, 2048>(mb + MB2 + r * 8192 + ht * 16, 4, v);
            const uint32_t a = SB + OFF_WA + ((ht >> 1) & 15) * 512 + ((ht >> 5) * 4 + (ht & 1) * 2) * 16;
            sts128(a, make_uint4(v[0].x, v[2].x, v[0].y, v[2].y));
            sts128(a + 16, make_uint4(v[0].z, v[2].z, v[0].w, v[2].w));
            sts128(a + 256, make_uint4(v[1].x, v[3].x, v[1].y, v[3].y));
            sts128(a + 272, make_uint4(v[1].z, v[3].z, v[1].w, v[3].w));
            bar_sync(9, 128);
        }
        if (ht == 0) TRACE(4);
        uint32_t qa[16][4];
#pragma unroll
        for (int s = 0; s < 16; s++) {
            const uint4 q = lds128(SB + OFF_WA + s * 512 + lane * 16);
            qa[s][0] = q.x; qa[s][1] = q.y; qa[s][2] = q.z; qa[s][3] = q.w;
        }
        __syncwarp();
        if (lane == 0) mbar_arrive(BAR(G_QA));
        const int nbs = (nk - (nt >> 1) + 1) >> 1;
        int sb = 0;
#pragma unroll 1
        for (int b = 0; b < nbs; b++) {
            if (b < nbg) mbar_wait(BAR(g_kv + b), 0);
            float c0[4] = {}, c1[4] = {}, c2[4] = {}, c3[4] = {};
#pragma unroll
            for (int i = 0; i < 4; i++) {
                uint32_t b0, b1, b2, b3, b4, b5, b6, b7;
                ldsm4(s_src0 + 2 * b * UNIT + i * 2048, b0, b1, b2, b3);
                ldsm4(s_src1 + 2 * b * UNIT + i * 2048, b4, b5, b6, b7);
                mma16816(c0, qa[4 * i][0], qa[4 * i][1], qa[4 * i][2], qa[4 * i][3], b0, b1);
                mma16816(c1, qa[4 * i + 1][0], qa[4 * i + 1][1], qa[4 * i + 1][2], qa[4 * i + 1][3], b2, b3);
                mma16816(c2, qa[4 * i + 2][0], qa[4 * i + 2][1], qa[4 * i + 2][2], qa[4 * i + 2][3], b4, b5);
                mma16816(c3, qa[4 * i + 3][0], qa[4 * i + 3][1], qa[4 * i + 3][2], qa[4 * i + 3][3], b6, b7);
            }
            if (b >= RS) pv_wait(SB + OFF_PVC, b - RS);
            st_async_v4(s_dst + slot_off(sb), __float_as_uint((c0[0] + c1[0]) + (c2[0] + c3[0])),
                        __float_as_uint((c0[1] + c1[1]) + (c2[1] + c3[1])), __float_as_uint((c0[2] + c1[2]) + (c2[2] + c3[2])),
                        __float_as_uint((c0[3] + c1[3]) + (c2[3] + c3[3])), s_bar + sb * 8);
            if (++sb == RS) sb = 0;
        }
        if (!full) return;
        if (nt < 2) {
            bar_sync(10, 320);
            delay(((P.dly >> 15) & 31) * 64);
            uint4 v[10];
            mb_poll<10, 1024>(mb + MB4 + h7 * 12288 + ht * 16, (tab.y >> 16) & 15, v);
            float a0 = 0.f, a1 = 0.f, a2 = 0.f, a3 = 0.f, e0 = 0.f, e1 = 0.f, e2 = 0.f, e3 = 0.f;
#pragma unroll
            for (int k = 0; k < 5; k++) {
                a0 += __uint_as_float(v[k].x); a1 += __uint_as_float(v[k].y);
                a2 += __uint_as_float(v[k].z); a3 += __uint_as_float(v[k].w);
                e0 += __uint_as_float(v[5 + k].x); e1 += __uint_as_float(v[5 + k].y);
                e2 += __uint_as_float(v[5 + k].z); e3 += __uint_as_float(v[5 + k].w);
            }
            bar_sync(4, 96);
            const float rl = __uint_as_float(lds32(SB + OFF_MISC));
            const uint32_t d = SB + OFF_CTX + frag_off(2 * ht);
            sts32(d, pack2((a0 + e0) * rl, (a1 + e1) * rl));
            sts32(d + 16, pack2((a2 + e2) * rl, (a3 + e3) * rl));
            asm volatile("bar.arrive 8, 320;" ::: "memory");
        } else if (nt == 2) {
            bar_sync(11, 288);
            delay(((P.dly >> 20) & 31) * 64);
            if (lane < 28) {
                const int w = (r & 1) * 56 + 2 * lane;
                const uint32_t d0 = SB + OFF_H + (r >> 1) * 448 + frag_off(w);
                uint32_t da[4], ba[4];
#pragma unroll
                for (int k = 0; k < 4; k++) { da[k] = mapa(d0, k); ba[k] = mapa(BAR(B_H), k); }
                uint4 v[16];
                mb_poll<16, 1792>(mb + MB5 + r * 448 + lane * 16, 16, v);
                float a[4][4] = {};
#pragma unroll
                for (int k = 0; k < 16; k++) {
                    a[k & 3][0] += __uint_as_float(v[k].x); a[k & 3][1] += __uint_as_float(v[k].y);
                    a[k & 3][2] += __uint_as_float(v[k].z); a[k & 3][3] += __uint_as_float(v[k].w);
                }
                const uint32_t h0 = pack2(bflo(xw0) + bf16r((a[0][0] + a[1][0]) + (a[2][0] + a[3][0])),
                                          bfhi(xw0) + bf16r((a[0][1] + a[1][1]) + (a[2][1] + a[3][1])));
                const uint32_t h1 = pack2(bflo(xw1) + bf16r((a[0][2] + a[1][2]) + (a[2][2] + a[3][2])),
                                          bfhi(xw1) + bf16r((a[0][3] + a[1][3]) + (a[2][3] + a[3][3])));
#pragma unroll
                for (int k = 0; k < 4; k++) {
                    st_async_b32(da[k], h0, ba[k]);
                    st_async_b32(da[k] + 16, h1, ba[k]);
                }
            }
        } else {
            const int k = (lane >> 1) & 3;
            mbar_wait(BAR(B_H), 0);
            {
                float v[14], mean, den;
#pragma unroll
                for (int i = 0; i < 7; i++) {
                    const uint32_t w = lds32(SB + OFF_H + (lane + 32 * i) * 4);
                    v[2 * i] = bflo(w); v[2 * i + 1] = bfhi(w);
                }
                ln_stats1(v, bflo(lds32(SB + OFF_H)), mean, den);
                if (lane == 0) {
                    sts32(SB + OFF_MISC + 8, __float_as_uint(mean));
                    sts32(SB + OFF_MISC + 12, __float_as_uint(__fdividef(1.f, den)));
                    mbar_arrive(BAR(B_GU));
                }
            }
            const uint32_t hw = lds32(SB + OFF_H + (r >> 1) * 448 + frag_off((r & 1) * 56 + j * 2 + (k >> 1)));
            uint4 v[4];
            const int n = lane < 4 ? 4 : lane < 8 ? 3 : 0;
            bar_sync(12, 288);
            delay(((P.dly >> 25) & 31) * 64);
            mb_poll<4, 256>(mb + MB6 + ((r * 28 + j) * 28 + lane) * 32, n, v);
            float v0 = (__uint_as_float(v[0].x) + __uint_as_float(v[1].x)) + (__uint_as_float(v[2].x) + __uint_as_float(v[3].x));
            float v1 = (__uint_as_float(v[0].y) + __uint_as_float(v[1].y)) + (__uint_as_float(v[2].y) + __uint_as_float(v[3].y));
            float v2 = (__uint_as_float(v[0].z) + __uint_as_float(v[1].z)) + (__uint_as_float(v[2].z) + __uint_as_float(v[3].z));
            float v3 = (__uint_as_float(v[0].w) + __uint_as_float(v[1].w)) + (__uint_as_float(v[2].w) + __uint_as_float(v[3].w));
            __syncwarp();
            const bool up = lane & 4;
            const float s0 = up ? v0 : v2, s1 = up ? v1 : v3;
            const float k0v = up ? v2 : v0, k1v = up ? v3 : v1;
            v0 = k0v + __shfl_xor_sync(~0u, s0, 4);
            v1 = k1v + __shfl_xor_sync(~0u, s1, 4);
            const bool up2 = lane & 2;
            const float s2 = up2 ? v0 : v1, k2v = up2 ? v1 : v0;
            v0 = k2v + __shfl_xor_sync(~0u, s2, 2);
            v0 += __shfl_xor_sync(~0u, v0, 1);
            if (lane < 8 && (lane & 1) == 0)
                P.out[r * 112 + j * 4 + k] = __float2bfloat16_rn(((k & 1) ? bfhi(hw) : bflo(hw)) + bf16r(v0));
            if (cta == 0 && lane == 0) g_epoch = epoch + 1;
            if (lane == 0) TRACE(13);
        }
        return;
    }
    if (warp >= 8) {
        const int sb = warp - 8, nt = lane >> 3, gg = (lane >> 2) & 1;
        if (lane == 0) {
            mbar_expect(BAR(B_S0 + sb), 2048);
            if (sb + 3 < RS) mbar_expect(BAR(B_S0 + sb + 3), 2048);
        }
        const uint32_t dst_a = mapa(SB + (nt >> 1) * 512 + ((r + 4 * gg) * 4 + t) * 16, (nt & 1) * 2);
        const uint32_t dst_b = mapa(SB + (nt >> 1) * 512 + ((r + 4 * gg) * 4 + t) * 16, (nt & 1) * 2 + 1);
        const uint32_t bar_a = mapa(BAR(B_P0), (nt & 1) * 2), bar_b = mapa(BAR(B_P0), (nt & 1) * 2 + 1);
        const uint32_t dst_m = mapa(SB + 1024 + (r + 4 * gg + 8 * nt) * 4, t), bar_m = mapa(BAR(B_P0), t);
        const uint32_t ref_prev = SB + OFF_REF + (sb == 0 ? 2 : sb - 1) * 16;
        asm volatile("barrier.cluster.wait.acquire.aligned;" ::: "memory");
#pragma unroll 1
        for (int b = sb; b < nb; b += 3) {
            const int si = b >= RS ? (b >= 2 * RS ? b - 2 * RS : b - RS) : b, sph = (b >= RS && b < 2 * RS) ? 1 : 0;
            const int pi = b >= RP ? (b >= 2 * RP ? b - 2 * RP : b - RP) : b;
            const uint32_t po = p_off(pi), bo = pi * 8, sa = SB + slot_off(si) + lane * 16;
            const bool valid = 2 * b + (nt >> 1) < nk;
            if (b >= RS) {
                const uint32_t tk = SB + OFF_REF + ((b - RS) % 3) * 16;
#pragma unroll 1
                for (int it = 0; it < SPIN_LIMIT * 8; it++)
                    if ((int)(lds128_vol(tk).x & 15u) > b - RS) break;
            }
            mbar_wait(BAR(B_S0 + si), sph);
            if (lane == 0 && b == 5) TRACE(16);
            const uint4 v0 = lds128(sa), v1 = lds128(sa + 512), v2 = lds128(sa + 1024), v3 = lds128(sa + 1536);
            float s0 = (__uint_as_float(v0.x) + __uint_as_float(v1.x)) + (__uint_as_float(v2.x) + __uint_as_float(v3.x));
            float s1 = (__uint_as_float(v0.y) + __uint_as_float(v1.y)) + (__uint_as_float(v2.y) + __uint_as_float(v3.y));
            float s2 = (__uint_as_float(v0.z) + __uint_as_float(v1.z)) + (__uint_as_float(v2.z) + __uint_as_float(v3.z));
            float s3 = (__uint_as_float(v0.w) + __uint_as_float(v1.w)) + (__uint_as_float(v2.w) + __uint_as_float(v3.w));
            const int i0 = valid ? f2o(fmaxf(s0, s1)) : INT_MIN, i1 = valid ? f2o(fmaxf(s2, s3)) : INT_MIN;
            int ra = __reduce_max_sync(~0u, gg ? INT_MIN : i0), rb = __reduce_max_sync(~0u, gg ? i0 : INT_MIN);
            int rc = __reduce_max_sync(~0u, gg ? INT_MIN : i1), rd = __reduce_max_sync(~0u, gg ? i1 : INT_MIN);
            ra = (ra + 15) & ~15; rb = (rb + 15) & ~15; rc = (rc + 15) & ~15; rd = (rd + 15) & ~15;
            if (b > 0) {
                uint4 pr;
#pragma unroll 1
                for (int it = 0; it < SPIN_LIMIT * 8; it++) {
                    pr = lds128_vol(ref_prev);
                    if ((int)(pr.x & pr.y & pr.z & pr.w & 15u) == b && (int)((pr.x | pr.y | pr.z | pr.w) & 15u) == b) break;
                }
                ra = max(ra, (int)pr.x - b); rb = max(rb, (int)pr.y - b); rc = max(rc, (int)pr.z - b); rd = max(rd, (int)pr.w - b);
            }
            __syncwarp();
            if (lane == 0) sts128_vol(SB + OFF_REF + sb * 16, make_uint4(ra | (b + 1), rb | (b + 1), rc | (b + 1), rd | (b + 1)));
            const float n0 = o2f(gg ? rb : ra), n1 = o2f(gg ? rd : rc);
            const uint32_t w0 = pack2(ex2(s0 - n0), ex2(s1 - n0)), w1 = pack2(ex2(s2 - n1), ex2(s3 - n1));
            const uint32_t o0 = __shfl_xor_sync(~0u, w0, 8), o1 = __shfl_xor_sync(~0u, w1, 8);
            if (lane < 16) st_async_b32(dst_m + po, __float_as_uint(nt ? n1 : n0), bar_m + bo);
            if (valid) {
                const bool odd = nt & 1;
                const uint32_t x0 = odd ? o0 : w0, x1 = odd ? o1 : w1, x2 = odd ? w0 : o0, x3 = odd ? w1 : o1;
                st_async_v4(dst_a + po, x0, x1, x2, x3, bar_a + bo);
                st_async_v4(dst_b + po, x0, x1, x2, x3, bar_b + bo);
            }
            if (lane == 0 && b == 5) TRACE(17);
            if (lane == 0 && b + RS < nb) mbar_expect(BAR(B_S0 + si), (2 * (b + RS) + 1 < nk) ? 2048 : 1024);
        }
        if (sb == 2) {
            bar_sync(5, 320);
            const unsigned char* mbp = g_mb + (epoch & 1) * MB_SET;
            const unsigned char* src = mbp + MB3 + (u0 + 8) * 1024 + lane * 16;
            const unsigned char* msrc = mbp + MBM + (((u0 + 8) >> 6) * NC_MAX + lane) * 32;
            const int n = nu > 8 ? ((16 + (lane >> 1) < NC) ? 2 : 1) : 0;
            const bool mact = nu > 8 && lane < NC;
            uint4 v[2];
            delay(((P.dly >> 10) & 31) * 64);
            mb_first<2, 512>(src, n, v);
            const uint32_t mj = mact ? mb_ld1(msrc) : (nu > 8 ? 0xff800000u : 0x3f800000u);
            combine_unit(SB, src, msrc, n, mact, v, mj, 8, lane);
            asm volatile("bar.arrive 3, 288;" ::: "memory");
        } else if (sb == 1) {
            bar_sync(5, 320);
            if (full) {
                const unsigned char* pm = g_mb + (epoch & 1) * MB_SET + MBM + (h7 * NC_MAX + lane) * 32;
                uint2 a = make_uint2(0xff800000u, 0);
                if (lane < NC) {
#pragma unroll 1
                    for (int it = 0; it < SPIN_LIMIT; it++) {
                        asm volatile("ld.relaxed.gpu.global.v2.u32 {%0,%1}, [%2];" : "=r"(a.x), "=r"(a.y) : "l"(pm) : "memory");
                        if (a.x != 0u) break;
                        __nanosleep(200);
                    }
                }
                __syncwarp();
                const float mj = __uint_as_float(a.x);
                float L = ex2(mj - o2f(__reduce_max_sync(~0u, f2o(mj)))) * __uint_as_float(a.y);
#pragma unroll
                for (int o = 16; o; o >>= 1) L += __shfl_xor_sync(~0u, L, o);
                if (lane == 0) sts32(SB + OFF_MISC, __float_as_uint(__fdividef(1.f, L)));
                asm volatile("bar.arrive 4, 96;" ::: "memory");
            }
        }
        return;
    }

    if (tid == 0) {
#pragma unroll 1
        for (int i = 0; i < RP; i++) mbar_expect(BAR(B_P0 + i), 1088);
        mbar_expect(BAR(B_H), 896);
        mbar_expect(BAR(B_GU), 2048);
    }
    const uint32_t o1 = MB1 + cta * 1024 + warp * 128 + lane * 8;
    const uint32_t o3 = MB3 + ((g * 64 + r * 16 + warp * 2) * NC_MAX + j) * 32 + t * 8;
    const bool a4 = g < 4 || hB != hA;
    const uint32_t o4 = MB4 + ((g < 4 ? hA : hB) * 12 + ((tab.y >> (g < 4 ? 8 : 12)) & 15)) * 1024 + warp * 128 + (lane & 15) * 8;
    const uint32_t o5 = MB5 + h7 * 1792 + mb7 * 256 + warp * 32 + t * 8;
    const int li6 = (warp + 8 * (g & 1)) * 4 + t;
    const bool a6 = g < 4 && ((g & 1) == 0 || warp < 6);
    const uint32_t o6 = MB6 + ((r * 28 + (li6 >> 1)) * 28 + j) * 32 + (g >> 1) * 16 + (li6 & 1) * 8;
    const bool am = tid < 32 && (g & 3) == r;
    const uint32_t om = MBM + (g * NC_MAX + j) * 32 + t * 8;
    const int ua = u0 + warp, ub = u0 + 8;
    const uint32_t o2a = MB2 + ((((ua & 63) >> 4) * 16 + (ua >> 6)) * 16 + (ua & 15)) * 32 + (lane >> 3) * 8;
    const uint32_t o2b = MB2 + ((((ub & 63) >> 4) * 16 + (ub >> 6)) * 16 + (ub & 15)) * 32 + (lane >> 3) * 8;
    if (full && lane < 16) mb_clear2(o1);
    if ((lane & 7) == 0) {
        mb_clear2(o2a);
        if (warp == 0 && nu > 8) mb_clear2(o2b);
    }
    unsigned char* const mb = g_mb + (epoch & 1) * MB_SET;

    if (full) {
        float v[14];
#pragma unroll
        for (int i = 0; i < 7; i++) { v[2 * i] = bflo(xr[i]); v[2 * i + 1] = bfhi(xr[i]); }
        float mean, den;
        ln_stats(v, mean, den);
        const float rden = __frcp_rn(den);
#pragma unroll
        for (int i = 0; i < 8; i++) xa[i] = pack2(ln_apply_r(bflo(xa[i]), mean, rden), ln_apply_r(bfhi(xa[i]), mean, rden));
        if (tid == 0) TRACE(14);
        float acc[4][4] = {};
        const int row = (lane & 7) + (lane & 8), ch = (warp & 1) * 4 + (lane >> 4);
        const uint32_t a0 = SB + OFF_CKV + 14 * UNIT + (warp >> 1) * 2048 + row * 128;
#pragma unroll
        for (int s = 0; s < 4; s++) {
            if ((s & 1) == 0) mbar_wait(BAR(s >> 1), 0);
            uint32_t b0, b1, b2, b3, b4, b5, b6, b7;
            ldsm4t(a0 + s * UNIT + ((ch ^ (row & 7)) << 4), b0, b1, b2, b3);
            ldsm4t(a0 + s * UNIT + (((ch + 2) ^ (row & 7)) << 4), b4, b5, b6, b7);
            mma16816(acc[0], xa[2 * s], 0, xa[2 * s + 1], 0, b0, b1);
            mma16816(acc[1], xa[2 * s], 0, xa[2 * s + 1], 0, b2, b3);
            mma16816(acc[2], xa[2 * s], 0, xa[2 * s + 1], 0, b4, b5);
            mma16816(acc[3], xa[2 * s], 0, xa[2 * s + 1], 0, b6, b7);
        }
        const float v0 = (g & 2) ? ((g & 1) ? acc[3][0] : acc[2][0]) : ((g & 1) ? acc[1][0] : acc[0][0]);
        const float v1 = (g & 2) ? ((g & 1) ? acc[3][1] : acc[2][1]) : ((g & 1) ? acc[1][1] : acc[0][1]);
        if (lane < 16) mb_put2f(mb + o1, v0, v1);
        __syncwarp();
        if (lane == 0) mbar_arrive(BAR(G_P1));
    }
    asm volatile("bar.arrive 13, 384;" ::: "memory");
    if (tid == 0) TRACE(1);
    mb_clear2(o3); mb_clear2(o3 + 1024); mb_clear2(o3 + 524288); mb_clear2(o3 + 524288 + 1024);
    if (a4) mb_clear2(o4);
    if (am) { mb_clear2(om); mb_clear2(om + 8 * NC_MAX * 32); }
    if (full) {
        if (lane < 4) mb_clear2(o5);
        if (a6) mb_clear2(o6);
    }
    bar_sync(7, 384);
    if (tid == 0) TRACE(2);
    {
        const int row = (lane & 7) + (lane & 8), cs = lane >> 4;
        const float sc = 0.0625f * 1.4426950408889634f;
        {
            const uint32_t qs = SB + OFF_QST + ((ua >> 6) != hA ? 512 : 0) + t * 16;
            uint4 q[8];
#pragma unroll
            for (int s2 = 0; s2 < 8; s2++) q[s2] = lds128(qs + s2 * 64);
            mbar_wait(BAR(g_uk + (warp >> 1)), 0);
            float c[4][4] = {};
            const uint32_t a0 = SB + OFF_WA + warp * UNIT + row * 128;
#pragma unroll
            for (int s2 = 0; s2 < 8; s2++) {
                uint32_t r0, r1, r2, r3, r4, r5, r6, r7;
                ldsm4(a0 + (s2 >> 1) * 2048 + ((((s2 & 1) * 4 + cs) ^ (row & 7)) << 4), r0, r1, r2, r3);
                ldsm4(a0 + (s2 >> 1) * 2048 + ((((s2 & 1) * 4 + 2 + cs) ^ (row & 7)) << 4), r4, r5, r6, r7);
                mma16816(c[(s2 & 1) * 2], r0, r1, r2, r3, q[s2].x, q[s2].y);
                mma16816(c[(s2 & 1) * 2 + 1], r4, r5, r6, r7, q[s2].z, q[s2].w);
            }
            const float lo = ((c[0][0] + c[1][0]) + (c[2][0] + c[3][0])) * sc, hi = ((c[0][2] + c[1][2]) + (c[2][2] + c[3][2])) * sc;
            const float lo2 = __shfl_down_sync(~0u, lo, 4), hi2 = __shfl_down_sync(~0u, hi, 4);
            if ((lane & 7) == 0) mb_put2(mb + o2a, pack2(lo, lo2), pack2(hi, hi2));
        }
        if (nu > 8 && warp == 0) {
            const uint32_t qs = SB + OFF_QST + ((ub >> 6) != hA ? 512 : 0) + t * 16;
            uint4 q[8];
#pragma unroll
            for (int s2 = 0; s2 < 8; s2++) q[s2] = lds128(qs + s2 * 64);
            mbar_wait(BAR(g_uk + 3), 0);
            float c[4][4] = {};
            const uint32_t a0 = SB + OFF_WA + 8 * UNIT + row * 128;
#pragma unroll
            for (int s2 = 0; s2 < 8; s2++) {
                uint32_t r0, r1, r2, r3, r4, r5, r6, r7;
                ldsm4(a0 + (s2 >> 1) * 2048 + ((((s2 & 1) * 4 + cs) ^ (row & 7)) << 4), r0, r1, r2, r3);
                ldsm4(a0 + (s2 >> 1) * 2048 + ((((s2 & 1) * 4 + 2 + cs) ^ (row & 7)) << 4), r4, r5, r6, r7);
                mma16816(c[(s2 & 1) * 2], r0, r1, r2, r3, q[s2].x, q[s2].y);
                mma16816(c[(s2 & 1) * 2 + 1], r4, r5, r6, r7, q[s2].z, q[s2].w);
            }
            const float lo = ((c[0][0] + c[1][0]) + (c[2][0] + c[3][0])) * sc, hi = ((c[0][2] + c[1][2]) + (c[2][2] + c[3][2])) * sc;
            const float lo2 = __shfl_down_sync(~0u, lo, 4), hi2 = __shfl_down_sync(~0u, hi, 4);
            if ((lane & 7) == 0) mb_put2(mb + o2b, pack2(lo, lo2), pack2(hi, hi2));
        }
    }
    if (tid == 0) TRACE(3);
    asm volatile("bar.arrive 6, 384;" ::: "memory");
    asm volatile("barrier.cluster.wait.acquire.aligned;" ::: "memory");
    {
        float acc[4][4] = {};
        float mr0 = -INFINITY, mr1 = -INFINITY, tl[4] = {};
        const int prow = (lane & 7) + (lane & 8), pch = (warp & 1) * 4 + (lane >> 4);
        const uint32_t p_src0 = SB + OFF_CKV + (warp >> 1) * 2048 + prow * 128 + ((pch ^ (prow & 7)) << 4);
        const uint32_t p_src1 = SB + OFF_CKV + (warp >> 1) * 2048 + prow * 128 + (((pch + 2) ^ (prow & 7)) << 4);
        const uint32_t one = 0x3f803f80u;
#pragma unroll 1
        for (int b = 0, pb = 0, pph = 0; b < nb; b++) {
            const bool two = 2 * b + 1 < nk;
            const uint32_t pbase = SB + p_off(pb);
            mbar_wait(BAR(B_P0 + pb), pph);
            if (tid == 0) TRACE(21 + b);
            uint32_t b0[8], b1[8];
            const float mb0 = __uint_as_float(lds32(pbase + 1024 + g * 4));
            const float mb1 = __uint_as_float(lds32(pbase + 1024 + 32 + g * 4));
            const uint4 p0 = lds128(pbase + lane * 16);
            ldsm4t(p_src0 + 2 * b * UNIT, b0[0], b0[1], b0[2], b0[3]);
            ldsm4t(p_src1 + 2 * b * UNIT, b0[4], b0[5], b0[6], b0[7]);
            uint4 p1;
            if (two) {
                p1 = lds128(pbase + 512 + lane * 16);
                ldsm4t(p_src0 + (2 * b + 1) * UNIT, b1[0], b1[1], b1[2], b1[3]);
                ldsm4t(p_src1 + (2 * b + 1) * UNIT, b1[4], b1[5], b1[6], b1[7]);
            }
            if (__any_sync(~0u, mb0 != mr0 || mb1 != mr1)) {
                const float al0 = ex2(mr0 - mb0), al1 = ex2(mr1 - mb1);
                mr0 = mb0; mr1 = mb1;
#pragma unroll
                for (int i = 0; i < 4; i++) { acc[i][0] *= al0; acc[i][1] *= al0; acc[i][2] *= al1; acc[i][3] *= al1; }
                tl[0] *= al0; tl[2] *= al1;
            }
#pragma unroll
            for (int i = 0; i < 4; i++) mma16816(acc[i], p0.x, p0.y, p0.z, p0.w, b0[2 * i], b0[2 * i + 1]);
            mma16816(tl, p0.x, p0.y, p0.z, p0.w, one, one);
            if (two) {
#pragma unroll
                for (int i = 0; i < 4; i++) mma16816(acc[i], p1.x, p1.y, p1.z, p1.w, b1[2 * i], b1[2 * i + 1]);
                mma16816(tl, p1.x, p1.y, p1.z, p1.w, one, one);
            }
            if (tid == 0 && b + RP < nb) mbar_expect(BAR(B_P0 + pb), (2 * (b + RP) + 1 < nk) ? 1088 : 576);
            __syncwarp();
            if (lane == 0) red_add(SB + OFF_PVC + b * 4, 1);
            if (++pb == RP) { pb = 0; pph ^= 1; }
        }
        if (am) {
            mb_put2f(mb + om, mr0, tl[0]);
            mb_put2f(mb + om + 8 * NC_MAX * 32, mr1, tl[2]);
        }
        mb_put2(mb + o3, pack2(acc[0][0], acc[0][1]), pack2(acc[1][0], acc[1][1]));
        mb_put2(mb + o3 + 1024, pack2(acc[2][0], acc[2][1]), pack2(acc[3][0], acc[3][1]));
        mb_put2(mb + o3 + 524288, pack2(acc[0][2], acc[0][3]), pack2(acc[1][2], acc[1][3]));
        mb_put2(mb + o3 + 524288 + 1024, pack2(acc[2][2], acc[2][3]), pack2(acc[3][2], acc[3][3]));
    }
    if (tid == 0) TRACE(5);
    {
        const uint32_t tpub = clock();
        const unsigned char* psrc = mb + MB3 + ua * 1024 + lane * 16;
        const int pn = (16 + (lane >> 1) < NC) ? 2 : 1;
        const unsigned char* msrc = mb + MBM + ((ua >> 6) * NC_MAX + lane) * 32;
        uint32_t mj = 0xff800000u;
        bar_sync(5, 320);
        uint32_t wb[9][8];
        const int p = (lane & 7) + (lane & 8);
        const int prow = ((p >> 1) & 1) * 8 + (p >> 2) * 2 + (p & 1), pch = (warp & 1) * 4 + (lane >> 4);
        const uint32_t src0 = SB + OFF_WA + (warp >> 1) * 2048 + prow * 128 + ((pch ^ (prow & 7)) << 4);
        const uint32_t src1 = SB + OFF_WA + (warp >> 1) * 2048 + prow * 128 + (((pch + 2) ^ (prow & 7)) << 4);
        uint4 pv[2];
#pragma unroll
        for (int ul = 0; ul < 9; ul++) {
            const uint32_t uo = (ul < 8 || nu > 8) ? ul * UNIT : 0;
            if ((ul & 1) == 0 && ul < 8) mbar_wait(BAR(g_uv + (ul >> 1)), 0);
            ldsm4t(src0 + uo, wb[ul][0], wb[ul][1], wb[ul][2], wb[ul][3]);
            ldsm4t(src1 + uo, wb[ul][4], wb[ul][5], wb[ul][6], wb[ul][7]);
        }
        while (clock() - tpub < ((P.dly >> 10) & 31) * 64) {}
        mb_first<2, 512>(psrc, pn, pv);
        if (lane < NC) mj = mb_ld1(msrc);
        if (tid == 0) TRACE(18);
        const int nA = (hA + 1) * 64 - u0;
        combine_unit(SB, psrc, msrc, pn, lane < NC, pv, mj, warp, lane);
        bar_sync(3, 288);
        if (tid == 0) TRACE(6);
        float acc[2][4][4] = {};
#pragma unroll
        for (int ul = 0; ul < 9; ul++) {
            const uint4 a = lds128((ul < nA) == (g < 4) ? SB + OFF_AFR + ul * 64 + t * 16 : SB + OFF_PVC + 48);
#pragma unroll
            for (int i = 0; i < 4; i++) mma16816(acc[ul & 1][i], a.x, a.y, a.z, a.w, wb[ul][2 * i], wb[ul][2 * i + 1]);
        }
        float v0, v1;
        {
            const int i = g & 3;
            float e[4][2];
#pragma unroll
            for (int k = 0; k < 4; k++) {
                e[k][0] = (acc[0][k][0] + acc[0][k][2]) + (acc[1][k][0] + acc[1][k][2]);
                e[k][1] = (acc[0][k][1] + acc[0][k][3]) + (acc[1][k][1] + acc[1][k][3]);
            }
            v0 = (i & 2) ? ((i & 1) ? e[3][0] : e[2][0]) : ((i & 1) ? e[1][0] : e[0][0]);
            v1 = (i & 2) ? ((i & 1) ? e[3][1] : e[2][1]) : ((i & 1) ? e[1][1] : e[0][1]);
        }
        if (a4) mb_put2f(mb + o4, v0, v1);
    }
    if (tid == 0) TRACE(7);
    if (!full) return;
    asm volatile("bar.arrive 10, 320;" ::: "memory");

    {
        mbar_wait(BAR(g_wo), 0);
        mbar_wait(BAR(g_wo + 1), 0);
        uint32_t b[8][4];
        const uint32_t src = SB + OFF_CKV + lane * 128 + ((warp ^ (lane & 7)) << 4);
#pragma unroll
        for (int s2 = 0; s2 < 8; s2++) ldsm4t(src + s2 * 4096, b[s2][0], b[s2][1], b[s2][2], b[s2][3]);
        bar_sync(8, 320);
        if (tid == 0) TRACE(8);
        float c[4][4] = {};
#pragma unroll
        for (int s2 = 0; s2 < 8; s2++) {
            const uint4 a = lds128(SB + OFF_CTX + s2 * 64 + t * 16);
            mma16816(c[(s2 & 1) * 2], a.x, 0, a.y, 0, b[s2][0], b[s2][1]);
            mma16816(c[(s2 & 1) * 2 + 1], a.z, 0, a.w, 0, b[s2][2], b[s2][3]);
        }
        if (lane < 4) mb_put2f(mb + o5, (c[0][0] + c[1][0]) + (c[2][0] + c[3][0]), (c[0][1] + c[1][1]) + (c[2][1] + c[3][1]));
    }
    asm volatile("bar.arrive 11, 288;" ::: "memory");
    if (tid == 0) TRACE(9);

    {
        mbar_wait(BAR(g_gu), 0);
        mbar_wait(BAR(g_gu + 1), 0);
        uint32_t b[7][4];
        const uint32_t src = SB + OFF_CKV + 4 * UNIT + lane * 128 + ((warp ^ (lane & 7)) << 4);
#pragma unroll
        for (int s2 = 0; s2 < 7; s2++) ldsm4t(src + s2 * 4096, b[s2][0], b[s2][1], b[s2][2], b[s2][3]);
        const uint32_t gdst = mapa(SB + OFF_GU + r * 512 + (warp * 4 + t) * 16, g & 3), gbar = mapa(BAR(B_GU), g & 3);
        mbar_wait(BAR(B_H), 0);
        if (tid == 0) TRACE(10);
        float c[4][4] = {};
        const uint32_t one = 0x3f803f80u;
#pragma unroll
        for (int s2 = 0; s2 < 7; s2++) {
            const uint4 a = lds128(SB + OFF_H + (r >> 1) * 448 + s2 * 64 + t * 16);
            mma16816(c[(s2 & 1) * 2], a.x, one, a.y, one, b[s2][0], b[s2][1]);
            mma16816(c[(s2 & 1) * 2 + 1], a.z, one, a.w, one, b[s2][2], b[s2][3]);
        }
        if (g < 4)
            st_async_v4(gdst, __float_as_uint((c[0][0] + c[1][0]) + (c[2][0] + c[3][0])),
                        __float_as_uint((c[0][1] + c[1][1]) + (c[2][1] + c[3][1])), __float_as_uint((c[0][2] + c[1][2]) + (c[2][2] + c[3][2])),
                        __float_as_uint((c[0][3] + c[1][3]) + (c[2][3] + c[3][3])), gbar);
    }
    {
        mbar_wait(BAR(g_wd), 0);
        uint32_t b[4][4];
        const uint32_t src = SB + OFF_CKV + 8 * UNIT + lane * 128 + ((warp ^ (lane & 7)) << 4);
        ldsm4t(src, b[0][0], b[0][1], b[0][2], b[0][3]);
        ldsm4t(src + 4096, b[1][0], b[1][1], b[1][2], b[1][3]);
        ldsm4t(src + UNIT, b[2][0], b[2][1], b[2][2], b[2][3]);
        ldsm4t(src + UNIT + 4096, b[3][0], b[3][1], b[3][2], b[3][3]);
        mbar_wait(BAR(B_GU), 0);
        if (tid == 0) TRACE(11);
        const uint32_t ga = SB + OFF_GU + (((g & 3) * 2 + (g >> 2)) * 4 + t) * 16;
        const uint4 p0 = lds128(ga), p1 = lds128(ga + 512), p2 = lds128(ga + 1024), p3 = lds128(ga + 1536);
        const float mean = __uint_as_float(lds32(SB + OFF_MISC + 8)), inv = __uint_as_float(lds32(SB + OFF_MISC + 12));
        const float g0 = bf16r(((__uint_as_float(p0.x) + __uint_as_float(p2.x)) - mean * (__uint_as_float(p0.z) + __uint_as_float(p2.z))) * inv);
        const float g1 = bf16r(((__uint_as_float(p0.y) + __uint_as_float(p2.y)) - mean * (__uint_as_float(p0.w) + __uint_as_float(p2.w))) * inv);
        const float u0v = bf16r(((__uint_as_float(p1.x) + __uint_as_float(p3.x)) - mean * (__uint_as_float(p1.z) + __uint_as_float(p3.z))) * inv);
        const float u1v = bf16r(((__uint_as_float(p1.y) + __uint_as_float(p3.y)) - mean * (__uint_as_float(p1.w) + __uint_as_float(p3.w))) * inv);
        const float s0 = bf16r(__fdividef(1.f, 1.f + __expf(-g0))), s1 = bf16r(__fdividef(1.f, 1.f + __expf(-g1)));
        const uint32_t hw = pack2(s0 * u0v, s1 * u1v);
        uint32_t a[8];
#pragma unroll
        for (int k = 0; k < 8; k++) a[k] = __shfl_sync(~0u, hw, k * 4 + t);
        float c0[4] = {}, c1[4] = {}, c2[4] = {}, c3[4] = {};
        mma16816(c0, a[0], 0, a[4], 0, b[0][0], b[0][1]);
        mma16816(c1, a[0], 0, a[4], 0, b[2][0], b[2][1]);
        mma16816(c2, a[1], 0, a[5], 0, b[0][2], b[0][3]);
        mma16816(c3, a[1], 0, a[5], 0, b[2][2], b[2][3]);
        mma16816(c0, a[2], 0, a[6], 0, b[1][0], b[1][1]);
        mma16816(c1, a[2], 0, a[6], 0, b[3][0], b[3][1]);
        mma16816(c2, a[3], 0, a[7], 0, b[1][2], b[1][3]);
        mma16816(c3, a[3], 0, a[7], 0, b[3][2], b[3][3]);
        if (a6) mb_put2f(mb + o6, (g & 1) ? c1[0] + c3[0] : c0[0] + c2[0], (g & 1) ? c1[1] + c3[1] : c0[1] + c2[1]);
    }
    asm volatile("bar.arrive 12, 288;" ::: "memory");
    if (tid == 0) TRACE(12);
}

__device__ float f_q[4096], f_qa[16 * 1024], f_s[16 * 8192], f_cc[64 * 16 * 1024], f_ctx[4096], f_h[448], f_hh[1792];

__device__ __forceinline__ void block_ln(const float* v  , float* o  ) {
    float a[14];
    const int lane = threadIdx.x & 31;
#pragma unroll
    for (int i = 0; i < 14; i++) a[i] = v[lane + 32 * i];
    float mb, den;
    ln_stats(a, mb, den);
    for (int i = threadIdx.x; i < 448; i += blockDim.x) o[i] = bf16r(ln_apply(v[i], mb, den));
    __syncthreads();
}
__global__ void fb_q(const __nv_bfloat16* x, const __nv_bfloat16* wq) {
    __shared__ float xs[448], xn[448];
    for (int i = threadIdx.x; i < 448; i += blockDim.x) xs[i] = __bfloat162float(x[i]);
    __syncthreads();
    block_ln(xs, xn);
    const int c = blockIdx.x * blockDim.x + threadIdx.x;
    float a = 0.f;
    for (int m = 0; m < 448; m++) a += xn[m] * __bfloat162float(wq[(size_t)m * 4096 + c]);
    f_q[c] = bf16r(a);
}
__global__ void fb_qabs(const __nv_bfloat16* wuk) {
    const int row = blockIdx.x * 8 + (threadIdx.x >> 5), lane = threadIdx.x & 31;
    const int h = row & 15, c = row >> 4;
    float a = 0.f;
    for (int d = lane; d < 256; d += 32) a += f_q[h * 256 + d] * __bfloat162float(wuk[(size_t)row * 256 + d]);
    for (int o = 16; o; o >>= 1) a += __shfl_xor_sync(~0u, a, o);
    if (lane == 0) f_qa[h * 1024 + c] = a * 0.0625f;
}
__global__ void fb_scores(const __nv_bfloat16* ckv) {
    const int k = blockIdx.x * 8 + (threadIdx.x >> 5), lane = threadIdx.x & 31;
    float a[16] = {};
    for (int c = lane; c < 1024; c += 32) {
        const float v = __bfloat162float(ckv[(size_t)k * 1024 + c]);
#pragma unroll
        for (int h = 0; h < 16; h++) a[h] += v * f_qa[h * 1024 + c];
    }
#pragma unroll
    for (int h = 0; h < 16; h++) {
        for (int o = 16; o; o >>= 1) a[h] += __shfl_xor_sync(~0u, a[h], o);
        if (lane == 0) f_s[h * 8192 + k] = a[h];
    }
}
__global__ void fb_softmax() {
    __shared__ float red[32];
    float* s = f_s + blockIdx.x * 8192;
    float m = -INFINITY;
    for (int i = threadIdx.x; i < 8192; i += blockDim.x) m = fmaxf(m, s[i]);
    for (int o = 16; o; o >>= 1) m = fmaxf(m, __shfl_xor_sync(~0u, m, o));
    if ((threadIdx.x & 31) == 0) red[threadIdx.x >> 5] = m;
    __syncthreads();
    m = red[0];
    for (int i = 1; i < (int)(blockDim.x >> 5); i++) m = fmaxf(m, red[i]);
    __syncthreads();
    float l = 0.f;
    for (int i = threadIdx.x; i < 8192; i += blockDim.x) { const float e = __expf(s[i] - m); s[i] = e; l += e; }
    for (int o = 16; o; o >>= 1) l += __shfl_xor_sync(~0u, l, o);
    if ((threadIdx.x & 31) == 0) red[threadIdx.x >> 5] = l;
    __syncthreads();
    l = 0.f;
    for (int i = 0; i < (int)(blockDim.x >> 5); i++) l += red[i];
    const float inv = 1.f / l;
    for (int i = threadIdx.x; i < 8192; i += blockDim.x) s[i] *= inv;
}
__global__ void fb_pv(const __nv_bfloat16* ckv) {
    const int c = blockIdx.y * 256 + threadIdx.x, kb = blockIdx.x * 128;
    float a[16] = {};
    for (int k = kb; k < kb + 128; k++) {
        const float v = __bfloat162float(ckv[(size_t)k * 1024 + c]);
#pragma unroll
        for (int h = 0; h < 16; h++) a[h] += v * f_s[h * 8192 + k];
    }
#pragma unroll
    for (int h = 0; h < 16; h++) f_cc[(blockIdx.x * 16 + h) * 1024 + c] = a[h];
}
__global__ void fb_ctx(const __nv_bfloat16* wuv) {
    __shared__ float cc[1024];
    const int h = blockIdx.x;
    for (int c = threadIdx.x; c < 1024; c += 256) {
        float a = 0.f;
        for (int i = 0; i < 64; i++) a += f_cc[(i * 16 + h) * 1024 + c];
        cc[c] = a;
    }
    __syncthreads();
    float a = 0.f;
    for (int c = 0; c < 1024; c++) a += cc[c] * __bfloat162float(wuv[(size_t)c * 4096 + h * 256 + threadIdx.x]);
    f_ctx[h * 256 + threadIdx.x] = bf16r(a);
}
__global__ void fb_o(const __nv_bfloat16* x, const __nv_bfloat16* wo) {
    __shared__ float red[8][32];
    const int m = blockIdx.x * 32 + (threadIdx.x & 31), p = threadIdx.x >> 5;
    float a = 0.f;
    for (int i = p * 512; i < p * 512 + 512; i++) a += f_ctx[i] * __bfloat162float(wo[(size_t)i * 448 + m]);
    red[p][threadIdx.x & 31] = a;
    __syncthreads();
    if (p == 0) {
        for (int i = 1; i < 8; i++) a += red[i][threadIdx.x];
        f_h[m] = bf16r(__bfloat162float(x[m]) + bf16r(a));
    }
}
__global__ void fb_gu(const __nv_bfloat16* wg, const __nv_bfloat16* wu) {
    __shared__ float hs[448], hn[448];
    for (int i = threadIdx.x; i < 448; i += blockDim.x) hs[i] = f_h[i];
    __syncthreads();
    block_ln(hs, hn);
    const int f = blockIdx.x * 64 + threadIdx.x;
    float a = 0.f, b = 0.f;
    for (int m = 0; m < 448; m++) {
        a += hn[m] * __bfloat162float(wg[(size_t)m * 1792 + f]);
        b += hn[m] * __bfloat162float(wu[(size_t)m * 1792 + f]);
    }
    f_hh[f] = bf16r(bf16r(1.f / (1.f + __expf(-bf16r(a)))) * bf16r(b));
}
__global__ void fb_down(const __nv_bfloat16* wd, __nv_bfloat16* out) {
    __shared__ float red[8][32];
    const int m = blockIdx.x * 32 + (threadIdx.x & 31), p = threadIdx.x >> 5;
    float a = 0.f;
    for (int i = p * 224; i < p * 224 + 224; i++) a += f_hh[i] * __bfloat162float(wd[(size_t)i * 448 + m]);
    red[p][threadIdx.x & 31] = a;
    __syncthreads();
    if (p == 0) {
        for (int i = 1; i < 8; i++) a += red[i][threadIdx.x];
        out[m] = __float2bfloat16_rn(f_h[m] + bf16r(a));
    }
}

typedef CUresult (*EncodeFn)(CUtensorMap*, CUtensorMapDataType, cuuint32_t, void*, const cuuint64_t*, const cuuint64_t*,
                             const cuuint32_t*, const cuuint32_t*, CUtensorMapInterleave, CUtensorMapSwizzle,
                             CUtensorMapL2promotion, CUtensorMapFloatOOBfill);

bool encode3(EncodeFn enc, CUtensorMap* m, const void* p, uint64_t rows, uint64_t rowbytes) {
    cuuint64_t dim[3] = {64, rows, rowbytes / 128};
    cuuint64_t str[2] = {rowbytes, 128};
    cuuint32_t box[3] = {64, 16, 4}, es[3] = {1, 1, 1};
    return enc(m, CU_TENSOR_MAP_DATA_TYPE_BFLOAT16, 3, const_cast<void*>(p), dim, str, box, es, CU_TENSOR_MAP_INTERLEAVE_NONE,
               CU_TENSOR_MAP_SWIZZLE_128B, CU_TENSOR_MAP_L2_PROMOTION_NONE, CU_TENSOR_MAP_FLOAT_OOB_FILL_NONE) == CUDA_SUCCESS;
}
bool encode2(EncodeFn enc, CUtensorMap* m, const void* p, uint64_t rows, uint64_t cols, uint32_t boxrows) {
    cuuint64_t dim[2] = {cols, rows};
    cuuint64_t str[1] = {cols * 2};
    cuuint32_t box[2] = {64, boxrows}, es[2] = {1, 1};
    return enc(m, CU_TENSOR_MAP_DATA_TYPE_BFLOAT16, 2, const_cast<void*>(p), dim, str, box, es, CU_TENSOR_MAP_INTERLEAVE_NONE,
               CU_TENSOR_MAP_SWIZZLE_128B, CU_TENSOR_MAP_L2_PROMOTION_NONE, CU_TENSOR_MAP_FLOAT_OOB_FILL_NONE) == CUDA_SUCCESS;
}

int g_force_fallback = 0;
int g_force_nc = 0;
int g_window = 0x2233;
unsigned g_dly = (24u << 10) | (8u << 15);

}

extern "C" void kernel_launch(void* const* d_in, const int* in_sizes, int n_in, void* d_out, int out_size) {
    const __nv_bfloat16* x = (const __nv_bfloat16*)d_in[0];
    const __nv_bfloat16* ckv = (const __nv_bfloat16*)d_in[1];
    const __nv_bfloat16* wq = (const __nv_bfloat16*)d_in[2];
    const __nv_bfloat16* wuk = (const __nv_bfloat16*)d_in[3];
    const __nv_bfloat16* wuv = (const __nv_bfloat16*)d_in[4];
    const __nv_bfloat16* wo = (const __nv_bfloat16*)d_in[5];
    const __nv_bfloat16* wg = (const __nv_bfloat16*)d_in[7];
    const __nv_bfloat16* wu = (const __nv_bfloat16*)d_in[8];
    const __nv_bfloat16* wd = (const __nv_bfloat16*)d_in[9];
    __nv_bfloat16* out = (__nv_bfloat16*)d_out;
    cudaStream_t st = cudaStreamPerThread;

    static int s_init = 0, s_nc = 0;
    static EncodeFn s_enc = nullptr;
    cudaLaunchConfig_t cfg = {};
    cudaLaunchAttribute at[1];
    at[0].id = cudaLaunchAttributeClusterDimension;
    at[0].val.clusterDim.x = 4; at[0].val.clusterDim.y = 1; at[0].val.clusterDim.z = 1;
    cfg.blockDim = dim3(NTHR); cfg.dynamicSmemBytes = SMEM_BYTES + 128; cfg.stream = st; cfg.attrs = at; cfg.numAttrs = 1;
    if (!s_init) {
        s_init = 1;
        void* fn = nullptr;
        cudaDriverEntryPointQueryResult qr;
        if (cudaGetDriverEntryPoint("cuTensorMapEncodeTiled", &fn, cudaEnableDefault, &qr) == cudaSuccess &&
            qr == cudaDriverEntryPointSuccess)
            s_enc = (EncodeFn)fn;
        int nc = 0;
        cfg.gridDim = dim3(4 * NC_MAX);
        if (cudaFuncSetAttribute(fused_kernel, cudaFuncAttributeMaxDynamicSharedMemorySize, SMEM_BYTES + 128) == cudaSuccess &&
            cudaOccupancyMaxActiveClusters(&nc, fused_kernel, &cfg) == cudaSuccess)
            s_nc = nc > NC_MAX ? NC_MAX : nc;
        (void)cudaGetLastError();
    }
    if (g_force_nc && g_force_nc < s_nc) s_nc = g_force_nc;
    Params P;
    bool ok = s_enc != nullptr && s_nc >= NC_MIN && !g_force_fallback;
    ok = ok && encode3(s_enc, &P.wq, wq, 448, 8192) && encode3(s_enc, &P.wuk, wuk, 1024, 8192) &&
         encode3(s_enc, &P.ckv, ckv, 8192, 2048) && encode3(s_enc, &P.wuv, wuv, 1024, 8192) &&
         encode2(s_enc, &P.wo, wo, 4096, 448, 64) && encode2(s_enc, &P.wg, wg, 448, 1792, 112) &&
         encode2(s_enc, &P.wu, wu, 448, 1792, 112) && encode2(s_enc, &P.wd, wd, 1792, 448, 64);
    if (ok) {
        P.x = x; P.out = out; P.NC = s_nc; P.W = g_window; P.dly = g_dly;
        const int N = 4 * s_nc;
        int ustart[4 * NC_MAX + 1], kstart[NC_MAX + 1];
        {
            const int kbase = 512 / s_nc, kext = 512 - kbase * s_nc;
            kstart[0] = 0;
            for (int jj = 0; jj < s_nc; jj++) kstart[jj + 1] = kstart[jj] + kbase + (jj >= s_nc - kext ? 1 : 0);
            int cap = 0;
            for (int c = 0; c < N; c++) cap += (kstart[(c >> 2) + 1] - kstart[c >> 2] > 17) ? 8 : 9;
            const bool deep = cap >= 1024;
            P.RS = deep ? 5 : 3;
            int nine = 0;
            for (int c = 0; c < N; c++) nine += (!deep || kstart[(c >> 2) + 1] - kstart[c >> 2] <= 17) ? 1 : 0;
            const int uext = 1024 - 8 * N;
            ustart[0] = 0;
            for (int c = 0, i = 0; c < N; c++) {
                int extra = 0;
                if (!deep || kstart[(c >> 2) + 1] - kstart[c >> 2] <= 17) { extra = (i + 1) * uext / nine - i * uext / nine; i++; }
                ustart[c + 1] = ustart[c] + 8 + extra;
            }
        }
        auto owner = [&](int u) { int c = 0; while (ustart[c + 1] <= u) c++; return c; };
        for (int c = 0; c < 4 * NC_MAX; c++) {
            if (c >= N) { P.tab[c] = make_uint2(0, 0); continue; }
            const int jj = c >> 2, u0 = ustart[c], nu = ustart[c + 1] - u0;
            const int k0 = kstart[jj], nk = kstart[jj + 1] - k0;
            const int h7 = (c / 7) & 15, mb7 = c % 7, hA = u0 >> 6, hB = (u0 + nu - 1) >> 6;
            const int ns = owner(h7 * 64 + 63) - owner(h7 * 64) + 1;
            P.tab[c].x = u0 | (nu << 10) | (k0 << 14) | (nk << 23);
            P.tab[c].y = h7 | (mb7 << 4) | ((c - owner(hA * 64)) << 8) | ((c - owner(hB * 64)) << 12) | (ns << 16);
        }
        cfg.gridDim = dim3(4 * s_nc);
        cudaLaunchKernelEx(&cfg, fused_kernel, P);
        return;
    }
    fb_q<<<16, 256, 0, st>>>(x, wq);
    fb_qabs<<<2048, 256, 0, st>>>(wuk);
    fb_scores<<<1024, 256, 0, st>>>(ckv);
    fb_softmax<<<16, 1024, 0, st>>>();
    fb_pv<<<dim3(64, 4), 256, 0, st>>>(ckv);
    fb_ctx<<<16, 256, 0, st>>>(wuv);
    fb_o<<<14, 256, 0, st>>>(x, wo);
    fb_gu<<<28, 64, 0, st>>>(wg, wu);
    fb_down<<<14, 256, 0, st>>>(wd, out);
}
```

```cpp
#include <cuda_runtime.h>
#include <cuda_bf16.h>
#include <cuda.h>
#include <stdint.h>
#include <limits.h>

namespace {

constexpr int NC_MAX = 32, NC_MIN = 29;
constexpr int NTHR = 512;

constexpr uint32_t UNIT = 8192;
constexpr uint32_t OFF_CKV = 0;
constexpr uint32_t OFF_WA = 18 * UNIT;
constexpr uint32_t OFF_X = OFF_WA + 9 * UNIT;
constexpr uint32_t OFF_SLOT = OFF_X;
constexpr uint32_t OFF_PBUF = OFF_X + 3 * 2048;
constexpr uint32_t PSTRIDE = 1088;
constexpr uint32_t OFF_BAR = OFF_PBUF + 4 * PSTRIDE;
constexpr uint32_t OFF_MISC = OFF_BAR + 42 * 8;
constexpr uint32_t OFF_WGT = OFF_CKV + 10 * UNIT;
constexpr uint32_t OFF_REF = OFF_MISC + 16;
constexpr uint32_t OFF_PVC = OFF_REF + 48;
constexpr uint32_t SMEM_BYTES = OFF_PVC + 64;
constexpr uint32_t OFF_QST = OFF_PBUF;
constexpr uint32_t OFF_TILE = OFF_X;
constexpr uint32_t OFF_CTX = OFF_X + 9216;
constexpr uint32_t OFF_AFR = OFF_X + 9728;
constexpr uint32_t OFF_H = OFF_X;
constexpr uint32_t OFF_GU = OFF_X + 1024;
static_assert(OFF_AFR + 576 <= OFF_BAR, "staging overflow");
static_assert(SMEM_BYTES + 128 <= 232448, "smem overflow");

enum { B_S0 = 26, B_P0 = 31, B_H = 37, B_GU = 38, G_P1 = 39, G_QA = 40, NBARS = 41 };

struct __align__(64) Params {
    CUtensorMap wq, wuk, ckv, wuv, wo, wg, wu, wd;
    const __nv_bfloat16* x;
    __nv_bfloat16* out;
    int NC;
    int W;
    unsigned dly;
    int RS;
    uint2 tab[4 * NC_MAX];
};

constexpr uint32_t MB1 = 0;
constexpr uint32_t MB2 = MB1 + 112 * 1024;
constexpr uint32_t MB3 = MB2 + 32768;
constexpr uint32_t MBM = MB3 + 1024 * 1024;
constexpr uint32_t MB4 = MBM + 16384;
constexpr uint32_t MB5 = MB4 + 16 * 12 * 1024;
constexpr uint32_t MB6 = MB5 + 16 * 1792;
constexpr uint32_t MB_SET = (MB6 + 4 * 28 * 28 * 32 + 1023) / 1024 * 1024;
__device__ __align__(1024) unsigned char g_mb[2 * MB_SET];
__device__ unsigned g_epoch;
#define TRACE(i) do {} while (0)

constexpr int SPIN_LIMIT = 1 << 18;
__device__ __forceinline__ void mbar_init(uint32_t b, uint32_t c) {
    asm volatile("mbarrier.init.shared::cta.b64 [%0], %1;" ::"r"(b), "r"(c) : "memory");
}
__device__ __forceinline__ void mbar_expect(uint32_t b, uint32_t bytes) {
    asm volatile("mbarrier.arrive.expect_tx.shared::cta.b64 _, [%0], %1;" ::"r"(b), "r"(bytes) : "memory");
}
__device__ __forceinline__ void mbar_arrive(uint32_t b) {
    asm volatile("mbarrier.arrive.shared::cta.b64 _, [%0];" ::"r"(b) : "memory");
}
__device__ __forceinline__ bool mbar_try(uint32_t b, uint32_t ph) {
    uint32_t ok;
    asm volatile("{.reg .pred p; mbarrier.try_wait.parity.shared::cta.b64 p, [%1], %2; selp.u32 %0,1,0,p;}"
                 : "=r"(ok) : "r"(b), "r"(ph) : "memory");
    return ok;
}
__device__ __forceinline__ bool mbar_test(uint32_t b, uint32_t ph) {
    uint32_t ok;
    asm volatile("{.reg .pred p; mbarrier.test_wait.parity.shared::cta.b64 p, [%1], %2; selp.u32 %0,1,0,p;}"
                 : "=r"(ok) : "r"(b), "r"(ph) : "memory");
    return ok;
}
__device__ __forceinline__ void mbar_wait(uint32_t b, uint32_t ph) {
#pragma unroll 1
    for (int i = 0; i < SPIN_LIMIT; i++)
        if (mbar_try(b, ph)) return;
}
__device__ __forceinline__ void mbar_wait_cl(uint32_t b, uint32_t ph) {
#pragma unroll 1
    for (int i = 0; i < SPIN_LIMIT; i++) {
        uint32_t ok;
        asm volatile("{.reg .pred p; mbarrier.try_wait.parity.acquire.cluster.shared::cta.b64 p, [%1], %2; selp.u32 %0,1,0,p;}"
                     : "=r"(ok) : "r"(b), "r"(ph) : "memory");
        if (ok) return;
    }
}
__device__ __forceinline__ void tma2p(uint32_t dst, const CUtensorMap* m, int x, int y, uint32_t bar, unsigned long long pol) {
    asm volatile("cp.async.bulk.tensor.2d.shared::cluster.global.mbarrier::complete_tx::bytes.L2::cache_hint [%0], [%1, {%3, %4}], [%2], %5;"
                 ::"r"(dst), "l"(m), "r"(bar), "r"(x), "r"(y), "l"(pol) : "memory");
}
__device__ __forceinline__ void tma3p(uint32_t dst, const CUtensorMap* m, int x, int y, int z, uint32_t bar, unsigned long long pol) {
    asm volatile("cp.async.bulk.tensor.3d.shared::cluster.global.mbarrier::complete_tx::bytes.L2::cache_hint [%0], [%1, {%3, %4, %5}], [%2], %6;"
                 ::"r"(dst), "l"(m), "r"(bar), "r"(x), "r"(y), "r"(z), "l"(pol) : "memory");
}
__device__ __forceinline__ uint32_t mapa(uint32_t a, uint32_t rank) {
    uint32_t r;
    asm("mapa.shared::cluster.u32 %0, %1, %2;" : "=r"(r) : "r"(a), "r"(rank));
    return r;
}
__device__ __forceinline__ void st_async_v4(uint32_t a, uint32_t x, uint32_t y, uint32_t z, uint32_t w, uint32_t bar) {
    asm volatile("st.async.weak.shared::cluster.mbarrier::complete_tx::bytes.v4.b32 [%0], {%1,%2,%3,%4}, [%5];"
                 ::"r"(a), "r"(x), "r"(y), "r"(z), "r"(w), "r"(bar) : "memory");
}
__device__ __forceinline__ void st_async_b32(uint32_t a, uint32_t x, uint32_t bar) {
    asm volatile("st.async.weak.shared::cluster.mbarrier::complete_tx::bytes.b32 [%0], %1, [%2];"
                 ::"r"(a), "r"(x), "r"(bar) : "memory");
}
__device__ __forceinline__ void ldsm4(uint32_t a, uint32_t& r0, uint32_t& r1, uint32_t& r2, uint32_t& r3) {
    asm volatile("ldmatrix.sync.aligned.m8n8.x4.shared.b16 {%0,%1,%2,%3}, [%4];"
                 : "=r"(r0), "=r"(r1), "=r"(r2), "=r"(r3) : "r"(a) : "memory");
}
__device__ __forceinline__ void ldsm4t(uint32_t a, uint32_t& r0, uint32_t& r1, uint32_t& r2, uint32_t& r3) {
    asm volatile("ldmatrix.sync.aligned.m8n8.x4.trans.shared.b16 {%0,%1,%2,%3}, [%4];"
                 : "=r"(r0), "=r"(r1), "=r"(r2), "=r"(r3) : "r"(a) : "memory");
}
__device__ __forceinline__ void mma16816(float (&c)[4], uint32_t a0, uint32_t a1, uint32_t a2, uint32_t a3, uint32_t b0, uint32_t b1) {
    asm("mma.sync.aligned.m16n8k16.row.col.f32.bf16.bf16.f32 {%0,%1,%2,%3}, {%4,%5,%6,%7}, {%8,%9}, {%0,%1,%2,%3};"
                 : "+f"(c[0]), "+f"(c[1]), "+f"(c[2]), "+f"(c[3]) : "r"(a0), "r"(a1), "r"(a2), "r"(a3), "r"(b0), "r"(b1));
}
__device__ __forceinline__ uint4 lds128(uint32_t a) {
    uint4 v;
    asm volatile("ld.shared.v4.u32 {%0,%1,%2,%3}, [%4];" : "=r"(v.x), "=r"(v.y), "=r"(v.z), "=r"(v.w) : "r"(a) : "memory");
    return v;
}
__device__ __forceinline__ uint32_t lds32(uint32_t a) {
    uint32_t v;
    asm volatile("ld.shared.u32 %0, [%1];" : "=r"(v) : "r"(a) : "memory");
    return v;
}
__device__ __forceinline__ uint32_t lds32_acq(uint32_t a) {
    uint32_t v;
    asm volatile("ld.acquire.cta.shared.u32 %0, [%1];" : "=r"(v) : "r"(a) : "memory");
    return v;
}
__device__ __forceinline__ uint4 lds128_vol(uint32_t a) {
    uint4 v;
    asm volatile("ld.volatile.shared.v4.u32 {%0,%1,%2,%3}, [%4];" : "=r"(v.x), "=r"(v.y), "=r"(v.z), "=r"(v.w) : "r"(a) : "memory");
    return v;
}
__device__ __forceinline__ void sts128_vol(uint32_t a, uint4 v) {
    asm volatile("st.volatile.shared.v4.u32 [%0], {%1,%2,%3,%4};" ::"r"(a), "r"(v.x), "r"(v.y), "r"(v.z), "r"(v.w) : "memory");
}
__device__ __forceinline__ void red_add_rel(uint32_t a, uint32_t v) {
    asm volatile("red.release.cta.shared.add.u32 [%0], %1;" ::"r"(a), "r"(v) : "memory");
}
__device__ __forceinline__ void pv_wait(uint32_t pvc, int k) {
#pragma unroll 1
    for (int it = 0; it < SPIN_LIMIT * 8; it++)
        if ((int)lds32_acq(pvc + k * 4) >= 8) return;
}
__device__ __forceinline__ void sts128(uint32_t a, uint4 v) {
    asm volatile("st.shared.v4.u32 [%0], {%1,%2,%3,%4};" ::"r"(a), "r"(v.x), "r"(v.y), "r"(v.z), "r"(v.w) : "memory");
}
__device__ __forceinline__ void sts32(uint32_t a, uint32_t v) {
    asm volatile("st.shared.u32 [%0], %1;" ::"r"(a), "r"(v) : "memory");
}
__device__ __forceinline__ void sts16(uint32_t a, uint16_t v) {
    asm volatile("st.shared.u16 [%0], %1;" ::"r"(a), "h"(v) : "memory");
}
__device__ __forceinline__ void bar_sync(int id, int n) {
    asm volatile("bar.sync %0, %1;" ::"r"(id), "r"(n) : "memory");
}
__device__ __forceinline__ float bf16r(float v) { return __bfloat162float(__float2bfloat16_rn(v)); }
__device__ __forceinline__ uint32_t pack2(float lo, float hi) {
    __nv_bfloat162 t = __floats2bfloat162_rn(lo, hi);
    return *reinterpret_cast<uint32_t*>(&t);
}
__device__ __forceinline__ float bflo(uint32_t w) { return __uint_as_float(w << 16); }
__device__ __forceinline__ float bfhi(uint32_t w) { return __uint_as_float(w & 0xffff0000u); }
__device__ __forceinline__ float ex2(float x) {
    float y;
    asm("ex2.approx.ftz.f32 %0, %1;" : "=f"(y) : "f"(x));
    return y;
}
__device__ __forceinline__ uint32_t ldg_early(const uint32_t* p) {
    uint32_t v;
    asm volatile("ld.global.nc.u32 %0, [%1];" : "=r"(v) : "l"(p));
    return v;
}

__device__ __forceinline__ void mb_st2(unsigned char* p, uint32_t a, uint32_t b) {
    asm volatile("st.relaxed.gpu.global.v2.u32 [%0], {%1,%2};" ::"l"(p), "r"(a), "r"(b) : "memory");
}
__device__ __forceinline__ void mb_put2(unsigned char* p, uint32_t a, uint32_t b) { mb_st2(p, a == 0u ? 0x80000000u : a, b); }
__device__ __forceinline__ void mb_put2f(unsigned char* p, float a, float b) { mb_put2(p, __float_as_uint(a), __float_as_uint(b)); }
__device__ __forceinline__ void mb_clear2(uint32_t off) {
    mb_st2(g_mb + off, 0u, 0u);
    mb_st2(g_mb + MB_SET + off, 0u, 0u);
}
__device__ __forceinline__ uint4 mb_ld4(const unsigned char* p) {
    uint4 v;
    asm volatile("ld.relaxed.gpu.global.v4.u32 {%0,%1,%2,%3}, [%4];" : "=r"(v.x), "=r"(v.y), "=r"(v.z), "=r"(v.w) : "l"(p) : "memory");
    return v;
}
template <int N, int STRIDE>
__device__ __forceinline__ void mb_poll(const unsigned char* p, int n, uint4 (&v)[N]) {
#pragma unroll
    for (int i = 0; i < N; i++) v[i] = i < n ? mb_ld4(p + i * STRIDE) : make_uint4(0, 0, 0, 0);
#pragma unroll 1
    for (int it = 0; it < SPIN_LIMIT; it++) {
        uint32_t m = 0xffffffffu;
#pragma unroll
        for (int i = 0; i < N; i++)
            if (i < n) m = min(m, min(v[i].x, v[i].z));
        if (m != 0u) break;
#pragma unroll
        for (int i = 0; i < N; i++)
            if (i < n && (N > 4 || min(v[i].x, v[i].z) == 0u)) v[i] = mb_ld4(p + i * STRIDE);
    }
}
__device__ __forceinline__ void delay(uint32_t clks) {
    const uint32_t t0 = clock();
    while (clock() - t0 < clks) {}
}

template <int N, int STRIDE>
__device__ __forceinline__ void mb_first(const unsigned char* p, int n, uint4 (&v)[N]) {
#pragma unroll
    for (int i = 0; i < N; i++) v[i] = i < n ? mb_ld4(p + i * STRIDE) : make_uint4(0, 0, 0, 0);
}
__device__ __forceinline__ void ln_stats(const float (&v)[14], float& mb, float& den) {
    float s = 0.f;
#pragma unroll
    for (int i = 0; i < 14; i++) s += v[i];
#pragma unroll
    for (int o = 16; o; o >>= 1) s += __shfl_xor_sync(~0u, s, o);
    const float mean = s * (1.f / 448.f);
    float q = 0.f;
#pragma unroll
    for (int i = 0; i < 14; i++) { const float d = v[i] - mean; q += d * d; }
#pragma unroll
    for (int o = 16; o; o >>= 1) q += __shfl_xor_sync(~0u, q, o);
    mb = bf16r(mean);
    den = bf16r(__fsqrt_rn(bf16r(bf16r(q * (1.f / 448.f)) + 1e-5f)));
}
__device__ __forceinline__ void ln_stats1(const float (&v)[14], float c, float& mb, float& den) {
    float s0 = 0.f, s1 = 0.f, q0 = 0.f, q1 = 0.f;
#pragma unroll
    for (int i = 0; i < 7; i++) {
        const float d0 = v[2 * i] - c, d1 = v[2 * i + 1] - c;
        s0 += d0; s1 += d1; q0 += d0 * d0; q1 += d1 * d1;
    }
    float s = s0 + s1, q = q0 + q1;
#pragma unroll
    for (int o = 16; o; o >>= 1) { s += __shfl_xor_sync(~0u, s, o); q += __shfl_xor_sync(~0u, q, o); }
    const float md = s * (1.f / 448.f);
    mb = bf16r(c + md);
    den = bf16r(__fsqrt_rn(bf16r(bf16r(fmaxf(q * (1.f / 448.f) - md * md, 0.f)) + 1e-5f)));
}
__device__ __forceinline__ float ln_apply(float v, float mb, float den) { return __fdiv_rn(bf16r(v - mb), den); }
__device__ __forceinline__ float ln_apply_r(float v, float mb, float rden) { return bf16r(v - mb) * rden; }

__device__ __forceinline__ uint32_t frag_off(int w) {
    const int s = w >> 3, half = (w >> 2) & 1, t = w & 3;
    return (uint32_t)((((s >> 1) * 4 + t) * 4 + (s & 1) * 2 + half) * 4);
}
__device__ __forceinline__ int f2o(float f) { const int i = __float_as_int(f); return i ^ ((i >> 31) & 0x7fffffff); }
__device__ __forceinline__ float o2f(int i) { return __int_as_float(i ^ ((i >> 31) & 0x7fffffff)); }

__device__ __forceinline__ uint32_t mb_ld1(const unsigned char* p) {
    uint32_t v;
    asm volatile("ld.relaxed.gpu.global.u32 %0, [%1];" : "=r"(v) : "l"(p) : "memory");
    return v;
}
__device__ __forceinline__ void combine_unit(uint32_t SB, const unsigned char* src, const unsigned char* msrc, int n, bool mact,
                                             uint4 (&v)[2], uint32_t mj, int ul, int lane) {
#pragma unroll 1
    for (int it = 0; it < SPIN_LIMIT; it++) {
        uint32_t m = mj;
        if (n > 0) m = min(m, min(v[0].x, v[0].z));
        if (n > 1) m = min(m, min(v[1].x, v[1].z));
        if (m != 0u) break;
        if (n > 0 && min(v[0].x, v[0].z) == 0u) v[0] = mb_ld4(src);
        if (n > 1 && min(v[1].x, v[1].z) == 0u) v[1] = mb_ld4(src + 512);
        if (mj == 0u) mj = mb_ld1(msrc);
    }
    __syncwarp();
    const uint32_t tile = SB + OFF_TILE + ul * 1024, wgt = SB + OFF_WGT + ul * 128;
    sts128(tile + lane * 16, v[0]);
    sts128(tile + 512 + lane * 16, v[1]);
    {
        const float mf = __uint_as_float(mj);
        const float w = ex2(mf - o2f(__reduce_max_sync(~0u, f2o(mf))));
        const int jj = lane & 15;
        const uint32_t d = wgt + ((lane >> 4) * 4 + ((jj & 7) >> 1)) * 16 + (jj >> 3) * 8 + (jj & 1) * 2;
        const __nv_bfloat16 hi = __float2bfloat16_rn(w), lo = __float2bfloat16_rn(w - __bfloat162float(hi));
        sts16(d, *reinterpret_cast<const uint16_t*>(&hi));
        sts16(d + 4, *reinterpret_cast<const uint16_t*>(&lo));
    }
    __syncwarp();
    const int t = lane & 3;
    uint32_t b[8];
    const uint32_t ts = tile + ((lane & 7) + (lane & 8)) * 32 + (lane >> 4) * 16;
    ldsm4t(ts, b[0], b[1], b[2], b[3]);
    ldsm4t(ts + 512, b[4], b[5], b[6], b[7]);
    const uint4 w0 = lds128(wgt + t * 16), w1 = lds128(wgt + 64 + t * 16);
    float c0[4] = {}, c1[4] = {}, c2[4] = {}, c3[4] = {};
    mma16816(c0, w0.x, w0.y, w0.z, w0.w, b[0], b[1]);
    mma16816(c1, w0.x, w0.y, w0.z, w0.w, b[2], b[3]);
    mma16816(c2, w1.x, w1.y, w1.z, w1.w, b[4], b[5]);
    mma16816(c3, w1.x, w1.y, w1.z, w1.w, b[6], b[7]);
    const float v0 = (c0[0] + c0[2]) + (c2[0] + c2[2]), v1 = (c0[1] + c0[3]) + (c2[1] + c2[3]);
    const float v2 = (c1[0] + c1[2]) + (c3[0] + c3[2]), v3 = (c1[1] + c1[3]) + (c3[1] + c3[3]);
    const uint32_t a0 = pack2(v0, v1), a2 = pack2(v2, v3);
    const uint32_t a1 = pack2(v0 - bflo(a0), v1 - bfhi(a0)), a3 = pack2(v2 - bflo(a2), v3 - bfhi(a2));
    if (lane < 4) sts128(SB + OFF_AFR + ul * 64 + t * 16, make_uint4(a0, a1, a2, a3));
}

__global__ void __launch_bounds__(NTHR, 1) fused_kernel(const __grid_constant__ Params P) {
    extern __shared__ __align__(1024) unsigned char smem_raw[];
    const uint32_t SB = (uint32_t)__cvta_generic_to_shared(smem_raw);
    const int tid = threadIdx.x, warp = tid >> 5, lane = tid & 31;
    const int g = lane >> 2, t = lane & 3;
    const int cta = blockIdx.x, j = cta >> 2, r = cta & 3;
    const uint2 tab = P.tab[cta];
    const int u0 = tab.x & 1023, nu = (tab.x >> 10) & 15, k0 = (tab.x >> 14) & 511, nk = (tab.x >> 23) & 31;
    const int h7 = tab.y & 15, mb7 = (tab.y >> 4) & 7;
    const bool full = cta < 112;
    const int nb = (nk + 1) >> 1, nbg = nk >> 1;
    const int g_uk = full ? 2 : 0, g_kv = g_uk + 4, g_uv = g_kv + nbg, g_wo = g_uv + 4, g_gu = g_wo + 2, g_wd = g_gu + 2;
    auto BAR = [&](int i) -> uint32_t { return SB + OFF_BAR + 8 * i; };

    if (warp == 11) {
        const int W1 = P.W & 15, W2 = (P.W >> 4) & 15, W3 = (P.W >> 8) & 15, W4 = (P.W >> 12) & 15, ngroups = full ? g_wd + 1 : g_wo;
        int done = 0;
        unsigned long long pol;
        asm volatile("createpolicy.fractional.L2::evict_first.b64 %0, 1.0;" : "=l"(pol));
        if (lane < 8) asm volatile("prefetch.tensormap [%0];" ::"l"(reinterpret_cast<const char*>(&P) + lane * 128) : "memory");
        if (lane == 0) {
            mbar_init(BAR(0), 1);
            mbar_init(BAR(1), 1);
            mbar_init(BAR(2), 1);
            mbar_init(BAR(3), 1);
            asm volatile("fence.mbarrier_init.release.cluster;" ::: "memory");
        }
        __syncwarp();
#pragma unroll 1
        for (int gi = 0; gi < ngroups; gi++) {
            if (gi == min(W1, 4)) {
                __syncthreads();
                asm volatile("barrier.cluster.arrive.relaxed.aligned;" ::: "memory");
            }
            const CUtensorMap* map;
            uint32_t dst, dstep = UNIT;
            int n = 2, x0 = 0, y0, z0 = -1, x1 = 0, y1, z1 = 0, y2 = 0, z2 = 0, gate = -1, pvgate = 0;
            if (gi < g_uk) {
                map = &P.wq; dst = OFF_CKV + (14 + 2 * gi) * UNIT;
                y0 = mb7 * 64 + gi * 32; y1 = y0 + 16; z0 = z1 = h7 * 4;
            } else if (gi < g_kv || (gi >= g_uv && gi < g_wo)) {
                const bool uv = gi >= g_uv;
                const int i0 = 2 * (gi - (uv ? g_uv : g_uk)), u = u0 + i0;
                if (gi == g_uv) gate = G_QA;
                map = uv ? &P.wuv : &P.wuk; dst = OFF_WA + i0 * UNIT; n = i0 == 6 ? nu - 6 : 2;
                y0 = (u & 63) * 16; z0 = (u >> 6) * 4; y1 = ((u + 1) & 63) * 16; z1 = ((u + 1) >> 6) * 4;
                y2 = ((u + 2) & 63) * 16; z2 = ((u + 2) >> 6) * 4;
            } else if (gi < g_uv) {
                const int b = gi - g_kv;
                if (b == 7 && full) gate = G_P1;
                map = &P.ckv; dst = OFF_CKV + 2 * b * UNIT; n = b == nbg - 1 ? nk - 2 * b : 2;
                y0 = (k0 + 2 * b) * 16; y1 = y0 + 16; y2 = y0 + 32; z0 = z1 = z2 = r * 4;
            } else if (gi < g_gu) {
                const int i = gi - g_wo;
                pvgate = 1;
                map = &P.wo; dst = OFF_CKV + 2 * i * UNIT;
                x0 = x1 = mb7 * 64; y0 = h7 * 256 + i * 128; y1 = y0 + 64;
            } else if (gi < g_wd) {
                const int i = gi - g_gu;
                pvgate = 3;
                map = (r & 1) ? &P.wu : &P.wg; dst = OFF_CKV + 4 * UNIT + i * 14336; n = 1; dstep = 14336;
                x0 = j * 64; y0 = (r >> 1) * 224 + i * 112; y1 = 0;
            } else {
                pvgate = 4;
                map = &P.wd; dst = OFF_CKV + 8 * UNIT;
                x0 = r * 112; x1 = x0 + 64; y0 = y1 = j * 64;
            }
            if (gate >= 0) mbar_wait(BAR(gate), 0);
            if (pvgate) pv_wait(SB + OFF_PVC, pvgate);
            {
                const int W = gi < g_kv ? W1 : gi < g_uv ? W2 : gi < g_wo ? W3 : W4;
#pragma unroll 1
                for (; done <= gi - W; done++) mbar_wait(BAR(done), 0);
            }
            if (lane == 0) {
                const uint32_t bar = BAR(gi);
                mbar_expect(bar, n * dstep);
                if (z0 >= 0) {
                    tma3p(SB + dst, map, 0, y0, z0, bar, pol);
                    tma3p(SB + dst + UNIT, map, 0, y1, z1, bar, pol);
                    if (n > 2) tma3p(SB + dst + 2 * UNIT, map, 0, y2, z2, bar, pol);
                } else {
                    tma2p(SB + dst, map, x0, y0, bar, pol);
                    if (n > 1) tma2p(SB + dst + UNIT, map, x1, y1, bar, pol);
                }
                if (gi == g_kv) TRACE(15);
                if (gi == g_uv) TRACE(19);
                if (gi == g_wo) TRACE(20);
            }
            __syncwarp();
        }
        if (lane == 0) TRACE(31);
        asm volatile("barrier.cluster.wait.acquire.aligned;" ::: "memory");
        return;
    }

    uint32_t epoch, xr[7], xa[8], xw0, xw1;
    {
        const uint32_t* x32 = reinterpret_cast<const uint32_t*>(P.x);
        asm volatile("ld.relaxed.gpu.global.u32 %0, [%1];" : "=r"(epoch) : "l"(&g_epoch) : "memory");
#pragma unroll
        for (int i = 0; i < 7; i++) xr[i] = ldg_early(x32 + lane + 32 * i);
#pragma unroll
        for (int i = 0; i < 8; i++) xa[i] = ldg_early(x32 + mb7 * 32 + (i >> 1) * 8 + (i & 1) * 4 + t);
        xw0 = ldg_early(x32 + r * 56 + 2 * min(lane, 27));
        xw1 = ldg_early(x32 + r * 56 + 2 * min(lane, 27) + 1);
    }
    if (lane == 0) {
#pragma unroll 1
        for (int i = 4 + (warp > 11 ? warp - 1 : warp); i < NBARS; i += 15) mbar_init(BAR(i), i == G_P1 ? 8 : i == G_QA ? 4 : i == B_GU ? 2 : 1);
        if (warp >= 8 && warp < 11) sts128(SB + OFF_REF + (warp - 8) * 16, make_uint4(0, 0, 0, 0));
        if (warp >= 12) sts128(SB + OFF_PVC + (warp - 12) * 16, make_uint4(0, 0, 0, 0));
        asm volatile("fence.mbarrier_init.release.cluster;" ::: "memory");
    }
    __syncthreads();
    asm volatile("barrier.cluster.arrive.relaxed.aligned;" ::: "memory");
    const int NC = P.NC;
    const int hA = u0 >> 6, hB = (u0 + nu - 1) >> 6;
    const int RS = P.RS, RP = RS + 1;
    const uint32_t xoff = nk <= 17 ? OFF_CKV + 17 * UNIT : OFF_WA + 8 * UNIT;
    auto slot_off = [&](int i) -> uint32_t { return i < 3 ? OFF_SLOT + i * 2048 : xoff + (i - 3) * 2048; };
    auto p_off = [&](int i) -> uint32_t { return i < 4 ? OFF_PBUF + i * PSTRIDE : xoff + 4096 + (i - 4) * PSTRIDE; };

    if (warp >= 12) {
        const int nt = warp - 12;
        const uint32_t s_dst = mapa(SB + r * 512 + (nt * 2 + (g >> 2)) * 64 + t * 16, g & 3);
        const uint32_t s_bar = mapa(BAR(B_S0), g & 3);
        const int srow = (nt & 1) * 8 + (lane & 7);
        const uint32_t s_src0 = SB + OFF_CKV + (nt >> 1) * UNIT + srow * 128 + (((lane >> 3) ^ (srow & 7)) << 4);
        const uint32_t s_src1 = SB + OFF_CKV + (nt >> 1) * UNIT + srow * 128 + (((4 + (lane >> 3)) ^ (srow & 7)) << 4);
        unsigned char* const mb = g_mb + (epoch & 1) * MB_SET;
        const int ht = tid - 384;
        bar_sync(13, 384);
        delay((P.dly & 31) * 64);
        if (ht < 64 || hB != hA) {
            const int i = ht & 63, hs = ht >> 6;
            uint4 v[7];
            mb_poll<7, 1024>(mb + MB1 + (hs ? hB : hA) * 7168 + i * 16, 7, v);
            float a0 = 0.f, a1 = 0.f, a2 = 0.f, a3 = 0.f;
#pragma unroll
            for (int k = 0; k < 7; k++) {
                a0 += __uint_as_float(v[k].x); a1 += __uint_as_float(v[k].y);
                a2 += __uint_as_float(v[k].z); a3 += __uint_as_float(v[k].w);
            }
            const uint32_t d = SB + OFF_QST + hs * 512 + frag_off(2 * i);
            sts32(d, pack2(a0, a1));
            sts32(d + 16, pack2(a2, a3));
        }
        asm volatile("bar.arrive 7, 384;" ::: "memory");
        asm volatile("barrier.cluster.wait.acquire.aligned;" ::: "memory");
        {
            bar_sync(6, 384);
            delay(((P.dly >> 5) & 31) * 64);
            uint4 v[4];
            mb_poll<4, 2048>(mb + MB2 + r * 8192 + ht * 16, 4, v);
            const uint32_t a = SB + OFF_WA + ((ht >> 1) & 15) * 512 + ((ht >> 5) * 4 + (ht & 1) * 2) * 16;
            sts128(a, make_uint4(v[0].x, v[2].x, v[0].y, v[2].y));
            sts128(a + 16, make_uint4(v[0].z, v[2].z, v[0].w, v[2].w));
            sts128(a + 256, make_uint4(v[1].x, v[3].x, v[1].y, v[3].y));
            sts128(a + 272, make_uint4(v[1].z, v[3].z, v[1].w, v[3].w));
            bar_sync(9, 128);
        }
        if (ht == 0) TRACE(4);
        uint32_t qa[16][4];
#pragma unroll
        for (int s = 0; s < 16; s++) {
            const uint4 q = lds128(SB + OFF_WA + s * 512 + lane * 16);
            qa[s][0] = q.x; qa[s][1] = q.y; qa[s][2] = q.z; qa[s][3] = q.w;
        }
        __syncwarp();
        if (lane == 0) mbar_arrive(BAR(G_QA));
        const int nbs = (nk - (nt >> 1) + 1) >> 1;
        int sb = 0;
        bool landed = false;
#pragma unroll 1
        for (int b = 0; b < nbs; b++) {
            if (!landed) mbar_wait(BAR(g_kv + b), 0);
            float c0[4] = {}, c1[4] = {}, c2[4] = {}, c3[4] = {};
#pragma unroll
            for (int i = 0; i < 4; i++) {
                uint32_t b0, b1, b2, b3, b4, b5, b6, b7;
                ldsm4(s_src0 + 2 * b * UNIT + i * 2048, b0, b1, b2, b3);
                ldsm4(s_src1 + 2 * b * UNIT + i * 2048, b4, b5, b6, b7);
                mma16816(c0, qa[4 * i][0], qa[4 * i][1], qa[4 * i][2], qa[4 * i][3], b0, b1);
                mma16816(c1, qa[4 * i + 1][0], qa[4 * i + 1][1], qa[4 * i + 1][2], qa[4 * i + 1][3], b2, b3);
                mma16816(c2, qa[4 * i + 2][0], qa[4 * i + 2][1], qa[4 * i + 2][2], qa[4 * i + 2][3], b4, b5);
                mma16816(c3, qa[4 * i + 3][0], qa[4 * i + 3][1], qa[4 * i + 3][2], qa[4 * i + 3][3], b6, b7);
            }
            landed = b + 1 >= nbg || mbar_test(BAR(g_kv + b + 1), 0);
            if (b >= RS) pv_wait(SB + OFF_PVC, b - RS);
            st_async_v4(s_dst + slot_off(sb), __float_as_uint((c0[0] + c1[0]) + (c2[0] + c3[0])),
                        __float_as_uint((c0[1] + c1[1]) + (c2[1] + c3[1])), __float_as_uint((c0[2] + c1[2]) + (c2[2] + c3[2])),
                        __float_as_uint((c0[3] + c1[3]) + (c2[3] + c3[3])), s_bar + sb * 8);
            if (++sb == RS) sb = 0;
        }
        if (!full) return;
        if (nt < 2) {
            bar_sync(10, 320);
            delay(((P.dly >> 15) & 31) * 64);
            uint4 v[10];
            mb_poll<10, 1024>(mb + MB4 + h7 * 12288 + ht * 16, (tab.y >> 16) & 15, v);
            float a0 = 0.f, a1 = 0.f, a2 = 0.f, a3 = 0.f, e0 = 0.f, e1 = 0.f, e2 = 0.f, e3 = 0.f;
#pragma unroll
            for (int k = 0; k < 5; k++) {
                a0 += __uint_as_float(v[k].x); a1 += __uint_as_float(v[k].y);
                a2 += __uint_as_float(v[k].z); a3 += __uint_as_float(v[k].w);
                e0 += __uint_as_float(v[5 + k].x); e1 += __uint_as_float(v[5 + k].y);
                e2 += __uint_as_float(v[5 + k].z); e3 += __uint_as_float(v[5 + k].w);
            }
            bar_sync(4, 96);
            const float rl = __uint_as_float(lds32(SB + OFF_MISC));
            const uint32_t d = SB + OFF_CTX + frag_off(2 * ht);
            sts32(d, pack2((a0 + e0) * rl, (a1 + e1) * rl));
            sts32(d + 16, pack2((a2 + e2) * rl, (a3 + e3) * rl));
            asm volatile("bar.arrive 8, 320;" ::: "memory");
        } else if (nt == 2) {
            bar_sync(11, 288);
            delay(((P.dly >> 20) & 31) * 64);
            if (lane < 28) {
                const int w = (r & 1) * 56 + 2 * lane;
                const uint32_t d0 = SB + OFF_H + (r >> 1) * 448 + frag_off(w);
                uint32_t da[4], ba[4];
#pragma unroll
                for (int k = 0; k < 4; k++) { da[k] = mapa(d0, k); ba[k] = mapa(BAR(B_H), k); }
                uint4 v[16];
                mb_poll<16, 1792>(mb + MB5 + r * 448 + lane * 16, 16, v);
                float a[4][4] = {};
#pragma unroll
                for (int k = 0; k < 16; k++) {
                    a[k & 3][0] += __uint_as_float(v[k].x); a[k & 3][1] += __uint_as_float(v[k].y);
                    a[k & 3][2] += __uint_as_float(v[k].z); a[k & 3][3] += __uint_as_float(v[k].w);
                }
                const uint32_t h0 = pack2(bflo(xw0) + bf16r((a[0][0] + a[1][0]) + (a[2][0] + a[3][0])),
                                          bfhi(xw0) + bf16r((a[0][1] + a[1][1]) + (a[2][1] + a[3][1])));
                const uint32_t h1 = pack2(bflo(xw1) + bf16r((a[0][2] + a[1][2]) + (a[2][2] + a[3][2])),
                                          bfhi(xw1) + bf16r((a[0][3] + a[1][3]) + (a[2][3] + a[3][3])));
#pragma unroll
                for (int k = 0; k < 4; k++) {
                    st_async_b32(da[k], h0, ba[k]);
                    st_async_b32(da[k] + 16, h1, ba[k]);
                }
            }
        } else {
            const int k = (lane >> 1) & 3;
            mbar_wait_cl(BAR(B_H), 0);
            {
                float v[14], mean, den;
#pragma unroll
                for (int i = 0; i < 7; i++) {
                    const uint32_t w = lds32(SB + OFF_H + (lane + 32 * i) * 4);
                    v[2 * i] = bflo(w); v[2 * i + 1] = bfhi(w);
                }
                ln_stats1(v, bflo(lds32(SB + OFF_H)), mean, den);
                if (lane == 0) {
                    sts32(SB + OFF_MISC + 8, __float_as_uint(mean));
                    sts32(SB + OFF_MISC + 12, __float_as_uint(__fdividef(1.f, den)));
                    mbar_arrive(BAR(B_GU));
                }
            }
            const uint32_t hw = lds32(SB + OFF_H + (r >> 1) * 448 + frag_off((r & 1) * 56 + j * 2 + (k >> 1)));
            uint4 v[4];
            const int n = lane < 4 ? 4 : lane < 8 ? 3 : 0;
            bar_sync(12, 288);
            delay(((P.dly >> 25) & 31) * 64);
            mb_poll<4, 256>(mb + MB6 + ((r * 28 + j) * 28 + lane) * 32, n, v);
            float v0 = (__uint_as_float(v[0].x) + __uint_as_float(v[1].x)) + (__uint_as_float(v[2].x) + __uint_as_float(v[3].x));
            float v1 = (__uint_as_float(v[0].y) + __uint_as_float(v[1].y)) + (__uint_as_float(v[2].y) + __uint_as_float(v[3].y));
            float v2 = (__uint_as_float(v[0].z) + __uint_as_float(v[1].z)) + (__uint_as_float(v[2].z) + __uint_as_float(v[3].z));
            float v3 = (__uint_as_float(v[0].w) + __uint_as_float(v[1].w)) + (__uint_as_float(v[2].w) + __uint_as_float(v[3].w));
            __syncwarp();
            const bool up = lane & 4;
            const float s0 = up ? v0 : v2, s1 = up ? v1 : v3;
            const float k0v = up ? v2 : v0, k1v = up ? v3 : v1;
            v0 = k0v + __shfl_xor_sync(~0u, s0, 4);
            v1 = k1v + __shfl_xor_sync(~0u, s1, 4);
            const bool up2 = lane & 2;
            const float s2 = up2 ? v0 : v1, k2v = up2 ? v1 : v0;
            v0 = k2v + __shfl_xor_sync(~0u, s2, 2);
            v0 += __shfl_xor_sync(~0u, v0, 1);
            if (lane < 8 && (lane & 1) == 0)
                P.out[r * 112 + j * 4 + k] = __float2bfloat16_rn(((k & 1) ? bfhi(hw) : bflo(hw)) + bf16r(v0));
            if (cta == 0 && lane == 0) g_epoch = epoch + 1;
            if (lane == 0) TRACE(13);
        }
        return;
    }
    if (warp >= 8) {
        const int sb = warp - 8, nt = lane >> 3, gg = (lane >> 2) & 1;
        if (lane == 0) {
            mbar_expect(BAR(B_S0 + sb), 2048);
            if (sb + 3 < RS) mbar_expect(BAR(B_S0 + sb + 3), 2048);
        }
        const uint32_t dst_a = mapa(SB + (nt >> 1) * 512 + ((r + 4 * gg) * 4 + t) * 16, (nt & 1) * 2);
        const uint32_t dst_b = mapa(SB + (nt >> 1) * 512 + ((r + 4 * gg) * 4 + t) * 16, (nt & 1) * 2 + 1);
        const uint32_t bar_a = mapa(BAR(B_P0), (nt & 1) * 2), bar_b = mapa(BAR(B_P0), (nt & 1) * 2 + 1);
        const uint32_t dst_m = mapa(SB + 1024 + (r + 4 * gg + 8 * nt) * 4, t), bar_m = mapa(BAR(B_P0), t);
        const uint32_t ref_prev = SB + OFF_REF + (sb == 0 ? 2 : sb - 1) * 16;
        asm volatile("barrier.cluster.wait.acquire.aligned;" ::: "memory");
#pragma unroll 1
        for (int b = sb; b < nb; b += 3) {
            const int si = b >= RS ? (b >= 2 * RS ? b - 2 * RS : b - RS) : b, sph = (b >= RS && b < 2 * RS) ? 1 : 0;
            const int pi = b >= RP ? (b >= 2 * RP ? b - 2 * RP : b - RP) : b;
            const uint32_t po = p_off(pi), bo = pi * 8, sa = SB + slot_off(si) + lane * 16;
            const bool valid = 2 * b + (nt >> 1) < nk;
            if (b >= RS) {
                const uint32_t tk = SB + OFF_REF + ((b - RS) % 3) * 16;
#pragma unroll 1
                for (int it = 0; it < SPIN_LIMIT * 8; it++)
                    if ((int)(lds128_vol(tk).x & 15u) > b - RS) break;
            }
            mbar_wait_cl(BAR(B_S0 + si), sph);
            if (lane == 0 && b == 5) TRACE(16);
            const uint4 v0 = lds128(sa), v1 = lds128(sa + 512), v2 = lds128(sa + 1024), v3 = lds128(sa + 1536);
            float s0 = (__uint_as_float(v0.x) + __uint_as_float(v1.x)) + (__uint_as_float(v2.x) + __uint_as_float(v3.x));
            float s1 = (__uint_as_float(v0.y) + __uint_as_float(v1.y)) + (__uint_as_float(v2.y) + __uint_as_float(v3.y));
            float s2 = (__uint_as_float(v0.z) + __uint_as_float(v1.z)) + (__uint_as_float(v2.z) + __uint_as_float(v3.z));
            float s3 = (__uint_as_float(v0.w) + __uint_as_float(v1.w)) + (__uint_as_float(v2.w) + __uint_as_float(v3.w));
            const int i0 = valid ? f2o(fmaxf(s0, s1)) : INT_MIN, i1 = valid ? f2o(fmaxf(s2, s3)) : INT_MIN;
            int ra = __reduce_max_sync(~0u, gg ? INT_MIN : i0), rb = __reduce_max_sync(~0u, gg ? i0 : INT_MIN);
            int rc = __reduce_max_sync(~0u, gg ? INT_MIN : i1), rd = __reduce_max_sync(~0u, gg ? i1 : INT_MIN);
            ra = (ra + 15) & ~15; rb = (rb + 15) & ~15; rc = (rc + 15) & ~15; rd = (rd + 15) & ~15;
            if (b > 0) {
                uint4 pr;
#pragma unroll 1
                for (int it = 0; it < SPIN_LIMIT * 8; it++) {
                    pr = lds128_vol(ref_prev);
                    if ((int)(pr.x & pr.y & pr.z & pr.w & 15u) == b && (int)((pr.x | pr.y | pr.z | pr.w) & 15u) == b) break;
                }
                ra = max(ra, (int)pr.x - b); rb = max(rb, (int)pr.y - b); rc = max(rc, (int)pr.z - b); rd = max(rd, (int)pr.w - b);
            }
            __syncwarp();
            if (lane == 0) sts128_vol(SB + OFF_REF + sb * 16, make_uint4(ra | (b + 1), rb | (b + 1), rc | (b + 1), rd | (b + 1)));
            const float n0 = o2f(gg ? rb : ra), n1 = o2f(gg ? rd : rc);
            const uint32_t w0 = pack2(ex2(s0 - n0), ex2(s1 - n0)), w1 = pack2(ex2(s2 - n1), ex2(s3 - n1));
            const uint32_t o0 = __shfl_xor_sync(~0u, w0, 8), o1 = __shfl_xor_sync(~0u, w1, 8);
            if (lane < 16) st_async_b32(dst_m + po, __float_as_uint(nt ? n1 : n0), bar_m + bo);
            if (valid) {
                const bool odd = nt & 1;
                const uint32_t x0 = odd ? o0 : w0, x1 = odd ? o1 : w1, x2 = odd ? w0 : o0, x3 = odd ? w1 : o1;
                st_async_v4(dst_a + po, x0, x1, x2, x3, bar_a + bo);
                st_async_v4(dst_b + po, x0, x1, x2, x3, bar_b + bo);
            }
            if (lane == 0 && b == 5) TRACE(17);
            if (lane == 0 && b + RS < nb) mbar_expect(BAR(B_S0 + si), (2 * (b + RS) + 1 < nk) ? 2048 : 1024);
        }
        if (sb == 2) {
            bar_sync(5, 320);
            const unsigned char* mbp = g_mb + (epoch & 1) * MB_SET;
            const unsigned char* src = mbp + MB3 + (u0 + 8) * 1024 + lane * 16;
            const unsigned char* msrc = mbp + MBM + (((u0 + 8) >> 6) * NC_MAX + lane) * 32;
            const int n = nu > 8 ? ((16 + (lane >> 1) < NC) ? 2 : 1) : 0;
            const bool mact = nu > 8 && lane < NC;
            uint4 v[2];
            delay(((P.dly >> 10) & 31) * 64);
            mb_first<2, 512>(src, n, v);
            const uint32_t mj = mact ? mb_ld1(msrc) : (nu > 8 ? 0xff800000u : 0x3f800000u);
            combine_unit(SB, src, msrc, n, mact, v, mj, 8, lane);
            asm volatile("bar.arrive 3, 288;" ::: "memory");
        } else if (sb == 1) {
            bar_sync(5, 320);
            if (full) {
                const unsigned char* pm = g_mb + (epoch & 1) * MB_SET + MBM + (h7 * NC_MAX + lane) * 32;
                uint2 a = make_uint2(0xff800000u, 0);
                if (lane < NC) {
#pragma unroll 1
                    for (int it = 0; it < SPIN_LIMIT; it++) {
                        asm volatile("ld.relaxed.gpu.global.v2.u32 {%0,%1}, [%2];" : "=r"(a.x), "=r"(a.y) : "l"(pm) : "memory");
                        if (a.x != 0u) break;
                        __nanosleep(200);
                    }
                }
                __syncwarp();
                const float mj = __uint_as_float(a.x);
                float L = ex2(mj - o2f(__reduce_max_sync(~0u, f2o(mj)))) * __uint_as_float(a.y);
#pragma unroll
                for (int o = 16; o; o >>= 1) L += __shfl_xor_sync(~0u, L, o);
                if (lane == 0) sts32(SB + OFF_MISC, __float_as_uint(__fdividef(1.f, L)));
                asm volatile("bar.arrive 4, 96;" ::: "memory");
            }
        }
        return;
    }

    if (tid == 0) {
#pragma unroll 1
        for (int i = 0; i < RP; i++) mbar_expect(BAR(B_P0 + i), 1088);
        mbar_expect(BAR(B_H), 896);
        mbar_expect(BAR(B_GU), 2048);
    }
    const uint32_t o1 = MB1 + cta * 1024 + warp * 128 + lane * 8;
    const uint32_t o3 = MB3 + ((g * 64 + r * 16 + warp * 2) * NC_MAX + j) * 32 + t * 8;
    const bool a4 = g < 4 || hB != hA;
    const uint32_t o4 = MB4 + ((g < 4 ? hA : hB) * 12 + ((tab.y >> (g < 4 ? 8 : 12)) & 15)) * 1024 + warp * 128 + (lane & 15) * 8;
    const uint32_t o5 = MB5 + h7 * 1792 + mb7 * 256 + warp * 32 + t * 8;
    const int li6 = (warp + 8 * (g & 1)) * 4 + t;
    const bool a6 = g < 4 && ((g & 1) == 0 || warp < 6);
    const uint32_t o6 = MB6 + ((r * 28 + (li6 >> 1)) * 28 + j) * 32 + (g >> 1) * 16 + (li6 & 1) * 8;
    const bool am = tid < 32 && (g & 3) == r;
    const uint32_t om = MBM + (g * NC_MAX + j) * 32 + t * 8;
    const int ua = u0 + warp, ub = u0 + 8;
    const uint32_t o2a = MB2 + ((((ua & 63) >> 4) * 16 + (ua >> 6)) * 16 + (ua & 15)) * 32 + (lane >> 3) * 8;
    const uint32_t o2b = MB2 + ((((ub & 63) >> 4) * 16 + (ub >> 6)) * 16 + (ub & 15)) * 32 + (lane >> 3) * 8;
    if (full && lane < 16) mb_clear2(o1);
    if ((lane & 7) == 0) {
        mb_clear2(o2a);
        if (warp == 0 && nu > 8) mb_clear2(o2b);
    }
    unsigned char* const mb = g_mb + (epoch & 1) * MB_SET;

    if (full) {
        float v[14];
#pragma unroll
        for (int i = 0; i < 7; i++) { v[2 * i] = bflo(xr[i]); v[2 * i + 1] = bfhi(xr[i]); }
        float mean, den;
        ln_stats(v, mean, den);
        const float rden = __frcp_rn(den);
#pragma unroll
        for (int i = 0; i < 8; i++) xa[i] = pack2(ln_apply_r(bflo(xa[i]), mean, rden), ln_apply_r(bfhi(xa[i]), mean, rden));
        if (tid == 0) TRACE(14);
        float acc[4][4] = {};
        const int row = (lane & 7) + (lane & 8), ch = (warp & 1) * 4 + (lane >> 4);
        const uint32_t a0 = SB + OFF_CKV + 14 * UNIT + (warp >> 1) * 2048 + row * 128;
#pragma unroll
        for (int s = 0; s < 4; s++) {
            if ((s & 1) == 0) mbar_wait(BAR(s >> 1), 0);
            uint32_t b0, b1, b2, b3, b4, b5, b6, b7;
            ldsm4t(a0 + s * UNIT + ((ch ^ (row & 7)) << 4), b0, b1, b2, b3);
            ldsm4t(a0 + s * UNIT + (((ch + 2) ^ (row & 7)) << 4), b4, b5, b6, b7);
            mma16816(acc[0], xa[2 * s], 0, xa[2 * s + 1], 0, b0, b1);
            mma16816(acc[1], xa[2 * s], 0, xa[2 * s + 1], 0, b2, b3);
            mma16816(acc[2], xa[2 * s], 0, xa[2 * s + 1], 0, b4, b5);
            mma16816(acc[3], xa[2 * s], 0, xa[2 * s + 1], 0, b6, b7);
        }
        const float v0 = (g & 2) ? ((g & 1) ? acc[3][0] : acc[2][0]) : ((g & 1) ? acc[1][0] : acc[0][0]);
        const float v1 = (g & 2) ? ((g & 1) ? acc[3][1] : acc[2][1]) : ((g & 1) ? acc[1][1] : acc[0][1]);
        if (lane < 16) mb_put2f(mb + o1, v0, v1);
        __syncwarp();
        if (lane == 0) mbar_arrive(BAR(G_P1));
    }
    asm volatile("bar.arrive 13, 384;" ::: "memory");
    if (tid == 0) TRACE(1);
    mb_clear2(o3); mb_clear2(o3 + 1024); mb_clear2(o3 + 524288); mb_clear2(o3 + 524288 + 1024);
    if (a4) mb_clear2(o4);
    if (am) { mb_clear2(om); mb_clear2(om + 8 * NC_MAX * 32); }
    if (full) {
        if (lane < 4) mb_clear2(o5);
        if (a6) mb_clear2(o6);
    }
    bar_sync(7, 384);
    if (tid == 0) TRACE(2);
    {
        const int row = (lane & 7) + (lane & 8), cs = lane >> 4;
        const float sc = 0.0625f * 1.4426950408889634f;
        {
            const uint32_t qs = SB + OFF_QST + ((ua >> 6) != hA ? 512 : 0) + t * 16;
            uint4 q[8];
#pragma unroll
            for (int s2 = 0; s2 < 8; s2++) q[s2] = lds128(qs + s2 * 64);
            mbar_wait(BAR(g_uk + (warp >> 1)), 0);
            float c[4][4] = {};
            const uint32_t a0 = SB + OFF_WA + warp * UNIT + row * 128;
#pragma unroll
            for (int s2 = 0; s2 < 8; s2++) {
                uint32_t r0, r1, r2, r3, r4, r5, r6, r7;
                ldsm4(a0 + (s2 >> 1) * 2048 + ((((s2 & 1) * 4 + cs) ^ (row & 7)) << 4), r0, r1, r2, r3);
                ldsm4(a0 + (s2 >> 1) * 2048 + ((((s2 & 1) * 4 + 2 + cs) ^ (row & 7)) << 4), r4, r5, r6, r7);
                mma16816(c[(s2 & 1) * 2], r0, r1, r2, r3, q[s2].x, q[s2].y);
                mma16816(c[(s2 & 1) * 2 + 1], r4, r5, r6, r7, q[s2].z, q[s2].w);
            }
            const float lo = ((c[0][0] + c[1][0]) + (c[2][0] + c[3][0])) * sc, hi = ((c[0][2] + c[1][2]) + (c[2][2] + c[3][2])) * sc;
            const float lo2 = __shfl_down_sync(~0u, lo, 4), hi2 = __shfl_down_sync(~0u, hi, 4);
            if ((lane & 7) == 0) mb_put2(mb + o2a, pack2(lo, lo2), pack2(hi, hi2));
        }
        if (nu > 8 && warp == 0) {
            const uint32_t qs = SB + OFF_QST + ((ub >> 6) != hA ? 512 : 0) + t * 16;
            uint4 q[8];
#pragma unroll
            for (int s2 = 0; s2 < 8; s2++) q[s2] = lds128(qs + s2 * 64);
            mbar_wait(BAR(g_uk + 3), 0);
            float c[4][4] = {};
            const uint32_t a0 = SB + OFF_WA + 8 * UNIT + row * 128;
#pragma unroll
            for (int s2 = 0; s2 < 8; s2++) {
                uint32_t r0, r1, r2, r3, r4, r5, r6, r7;
                ldsm4(a0 + (s2 >> 1) * 2048 + ((((s2 & 1) * 4 + cs) ^ (row & 7)) << 4), r0, r1, r2, r3);
                ldsm4(a0 + (s2 >> 1) * 2048 + ((((s2 & 1) * 4 + 2 + cs) ^ (row & 7)) << 4), r4, r5, r6, r7);
                mma16816(c[(s2 & 1) * 2], r0, r1, r2, r3, q[s2].x, q[s2].y);
                mma16816(c[(s2 & 1) * 2 + 1], r4, r5, r6, r7, q[s2].z, q[s2].w);
            }
            const float lo = ((c[0][0] + c[1][0]) + (c[2][0] + c[3][0])) * sc, hi = ((c[0][2] + c[1][2]) + (c[2][2] + c[3][2])) * sc;
            const float lo2 = __shfl_down_sync(~0u, lo, 4), hi2 = __shfl_down_sync(~0u, hi, 4);
            if ((lane & 7) == 0) mb_put2(mb + o2b, pack2(lo, lo2), pack2(hi, hi2));
        }
    }
    if (tid == 0) TRACE(3);
    asm volatile("bar.arrive 6, 384;" ::: "memory");
    asm volatile("barrier.cluster.wait.acquire.aligned;" ::: "memory");
    {
        float acc[4][4] = {};
        float mr0 = -INFINITY, mr1 = -INFINITY, tl[4] = {};
        const int prow = (lane & 7) + (lane & 8), pch = (warp & 1) * 4 + (lane >> 4);
        const uint32_t p_src0 = SB + OFF_CKV + (warp >> 1) * 2048 + prow * 128 + ((pch ^ (prow & 7)) << 4);
        const uint32_t p_src1 = SB + OFF_CKV + (warp >> 1) * 2048 + prow * 128 + (((pch + 2) ^ (prow & 7)) << 4);
        const uint32_t one = 0x3f803f80u;
#pragma unroll 1
        for (int b = 0, pb = 0, pph = 0; b < nb; b++) {
            const bool two = 2 * b + 1 < nk;
            const uint32_t pbase = SB + p_off(pb);
            mbar_wait_cl(BAR(B_P0 + pb), pph);
            if (tid == 0) TRACE(21 + b);
            uint32_t b0[8], b1[8];
            const float mb0 = __uint_as_float(lds32(pbase + 1024 + g * 4));
            const float mb1 = __uint_as_float(lds32(pbase + 1024 + 32 + g * 4));
            const uint4 p0 = lds128(pbase + lane * 16);
            ldsm4t(p_src0 + 2 * b * UNIT, b0[0], b0[1], b0[2], b0[3]);
            ldsm4t(p_src1 + 2 * b * UNIT, b0[4], b0[5], b0[6], b0[7]);
            uint4 p1;
            if (two) {
                p1 = lds128(pbase + 512 + lane * 16);
                ldsm4t(p_src0 + (2 * b + 1) * UNIT, b1[0], b1[1], b1[2], b1[3]);
                ldsm4t(p_src1 + (2 * b + 1) * UNIT, b1[4], b1[5], b1[6], b1[7]);
            }
            if (__any_sync(~0u, mb0 != mr0 || mb1 != mr1)) {
                const float al0 = ex2(mr0 - mb0), al1 = ex2(mr1 - mb1);
                mr0 = mb0; mr1 = mb1;
#pragma unroll
                for (int i = 0; i < 4; i++) { acc[i][0] *= al0; acc[i][1] *= al0; acc[i][2] *= al1; acc[i][3] *= al1; }
                tl[0] *= al0; tl[2] *= al1;
            }
#pragma unroll
            for (int i = 0; i < 4; i++) mma16816(acc[i], p0.x, p0.y, p0.z, p0.w, b0[2 * i], b0[2 * i + 1]);
            mma16816(tl, p0.x, p0.y, p0.z, p0.w, one, one);
            if (two) {
#pragma unroll
                for (int i = 0; i < 4; i++) mma16816(acc[i], p1.x, p1.y, p1.z, p1.w, b1[2 * i], b1[2 * i + 1]);
                mma16816(tl, p1.x, p1.y, p1.z, p1.w, one, one);
            }
            if (tid == 0 && b + RP < nb) mbar_expect(BAR(B_P0 + pb), (2 * (b + RP) + 1 < nk) ? 1088 : 576);
            __syncwarp();
            if (lane == 0) red_add_rel(SB + OFF_PVC + b * 4, 1);
            if (++pb == RP) { pb = 0; pph ^= 1; }
        }
        if (am) {
            mb_put2f(mb + om, mr0, tl[0]);
            mb_put2f(mb + om + 8 * NC_MAX * 32, mr1, tl[2]);
        }
        mb_put2(mb + o3, pack2(acc[0][0], acc[0][1]), pack2(acc[1][0], acc[1][1]));
        mb_put2(mb + o3 + 1024, pack2(acc[2][0], acc[2][1]), pack2(acc[3][0], acc[3][1]));
        mb_put2(mb + o3 + 524288, pack2(acc[0][2], acc[0][3]), pack2(acc[1][2], acc[1][3]));
        mb_put2(mb + o3 + 524288 + 1024, pack2(acc[2][2], acc[2][3]), pack2(acc[3][2], acc[3][3]));
    }
    if (tid == 0) TRACE(5);
    {
        const uint32_t tpub = clock();
        const unsigned char* psrc = mb + MB3 + ua * 1024 + lane * 16;
        const int pn = (16 + (lane >> 1) < NC) ? 2 : 1;
        const unsigned char* msrc = mb + MBM + ((ua >> 6) * NC_MAX + lane) * 32;
        uint32_t mj = 0xff800000u;
        bar_sync(5, 320);
        uint32_t wb[9][8];
        const int p = (lane & 7) + (lane & 8);
        const int prow = ((p >> 1) & 1) * 8 + (p >> 2) * 2 + (p & 1), pch = (warp & 1) * 4 + (lane >> 4);
        const uint32_t src0 = SB + OFF_WA + (warp >> 1) * 2048 + prow * 128 + ((pch ^ (prow & 7)) << 4);
        const uint32_t src1 = SB + OFF_WA + (warp >> 1) * 2048 + prow * 128 + (((pch + 2) ^ (prow & 7)) << 4);
        uint4 pv[2];
#pragma unroll
        for (int ul = 0; ul < 9; ul++) {
            const uint32_t uo = (ul < 8 || nu > 8) ? ul * UNIT : 0;
            if ((ul & 1) == 0 && ul < 8) mbar_wait(BAR(g_uv + (ul >> 1)), 0);
            ldsm4t(src0 + uo, wb[ul][0], wb[ul][1], wb[ul][2], wb[ul][3]);
            ldsm4t(src1 + uo, wb[ul][4], wb[ul][5], wb[ul][6], wb[ul][7]);
        }
        while (clock() - tpub < ((P.dly >> 10) & 31) * 64) {}
        mb_first<2, 512>(psrc, pn, pv);
        if (lane < NC) mj = mb_ld1(msrc);
        if (tid == 0) TRACE(18);
        const int nA = (hA + 1) * 64 - u0;
        combine_unit(SB, psrc, msrc, pn, lane < NC, pv, mj, warp, lane);
        bar_sync(3, 288);
        if (tid == 0) TRACE(6);
        float acc[2][4][4] = {};
#pragma unroll
        for (int ul = 0; ul < 9; ul++) {
            const uint4 a = lds128((ul < nA) == (g < 4) ? SB + OFF_AFR + ul * 64 + t * 16 : SB + OFF_PVC + 48);
#pragma unroll
            for (int i = 0; i < 4; i++) mma16816(acc[ul & 1][i], a.x, a.y, a.z, a.w, wb[ul][2 * i], wb[ul][2 * i + 1]);
        }
        float v0, v1;
        {
            const int i = g & 3;
            float e[4][2];
#pragma unroll
            for (int k = 0; k < 4; k++) {
                e[k][0] = (acc[0][k][0] + acc[0][k][2]) + (acc[1][k][0] + acc[1][k][2]);
                e[k][1] = (acc[0][k][1] + acc[0][k][3]) + (acc[1][k][1] + acc[1][k][3]);
            }
            v0 = (i & 2) ? ((i & 1) ? e[3][0] : e[2][0]) : ((i & 1) ? e[1][0] : e[0][0]);
            v1 = (i & 2) ? ((i & 1) ? e[3][1] : e[2][1]) : ((i & 1) ? e[1][1] : e[0][1]);
        }
        if (a4) mb_put2f(mb + o4, v0, v1);
    }
    if (tid == 0) TRACE(7);
    if (!full) return;
    asm volatile("bar.arrive 10, 320;" ::: "memory");

    {
        mbar_wait(BAR(g_wo), 0);
        mbar_wait(BAR(g_wo + 1), 0);
        uint32_t b[8][4];
        const uint32_t src = SB + OFF_CKV + lane * 128 + ((warp ^ (lane & 7)) << 4);
#pragma unroll
        for (int s2 = 0; s2 < 8; s2++) ldsm4t(src + s2 * 4096, b[s2][0], b[s2][1], b[s2][2], b[s2][3]);
        bar_sync(8, 320);
        if (tid == 0) TRACE(8);
        float c[4][4] = {};
#pragma unroll
        for (int s2 = 0; s2 < 8; s2++) {
            const uint4 a = lds128(SB + OFF_CTX + s2 * 64 + t * 16);
            mma16816(c[(s2 & 1) * 2], a.x, 0, a.y, 0, b[s2][0], b[s2][1]);
            mma16816(c[(s2 & 1) * 2 + 1], a.z, 0, a.w, 0, b[s2][2], b[s2][3]);
        }
        if (lane < 4) mb_put2f(mb + o5, (c[0][0] + c[1][0]) + (c[2][0] + c[3][0]), (c[0][1] + c[1][1]) + (c[2][1] + c[3][1]));
    }
    asm volatile("bar.arrive 11, 288;" ::: "memory");
    if (tid == 0) TRACE(9);

    {
        mbar_wait(BAR(g_gu), 0);
        mbar_wait(BAR(g_gu + 1), 0);
        uint32_t b[7][4];
        const uint32_t src = SB + OFF_CKV + 4 * UNIT + lane * 128 + ((warp ^ (lane & 7)) << 4);
#pragma unroll
        for (int s2 = 0; s2 < 7; s2++) ldsm4t(src + s2 * 4096, b[s2][0], b[s2][1], b[s2][2], b[s2][3]);
        const uint32_t gdst = mapa(SB + OFF_GU + r * 512 + (warp * 4 + t) * 16, g & 3), gbar = mapa(BAR(B_GU), g & 3);
        mbar_wait_cl(BAR(B_H), 0);
        if (tid == 0) TRACE(10);
        float c[4][4] = {};
        const uint32_t one = 0x3f803f80u;
#pragma unroll
        for (int s2 = 0; s2 < 7; s2++) {
            const uint4 a = lds128(SB + OFF_H + (r >> 1) * 448 + s2 * 64 + t * 16);
            mma16816(c[(s2 & 1) * 2], a.x, one, a.y, one, b[s2][0], b[s2][1]);
            mma16816(c[(s2 & 1) * 2 + 1], a.z, one, a.w, one, b[s2][2], b[s2][3]);
        }
        if (g < 4)
            st_async_v4(gdst, __float_as_uint((c[0][0] + c[1][0]) + (c[2][0] + c[3][0])),
                        __float_as_uint((c[0][1] + c[1][1]) + (c[2][1] + c[3][1])), __float_as_uint((c[0][2] + c[1][2]) + (c[2][2] + c[3][2])),
                        __float_as_uint((c[0][3] + c[1][3]) + (c[2][3] + c[3][3])), gbar);
    }
    {
        mbar_wait(BAR(g_wd), 0);
        uint32_t b[4][4];
        const uint32_t src = SB + OFF_CKV + 8 * UNIT + lane * 128 + ((warp ^ (lane & 7)) << 4);
        ldsm4t(src, b[0][0], b[0][1], b[0][2], b[0][3]);
        ldsm4t(src + 4096, b[1][0], b[1][1], b[1][2], b[1][3]);
        ldsm4t(src + UNIT, b[2][0], b[2][1], b[2][2], b[2][3]);
        ldsm4t(src + UNIT + 4096, b[3][0], b[3][1], b[3][2], b[3][3]);
        mbar_wait_cl(BAR(B_GU), 0);
        if (tid == 0) TRACE(11);
        const uint32_t ga = SB + OFF_GU + (((g & 3) * 2 + (g >> 2)) * 4 + t) * 16;
        const uint4 p0 = lds128(ga), p1 = lds128(ga + 512), p2 = lds128(ga + 1024), p3 = lds128(ga + 1536);
        const float mean = __uint_as_float(lds32(SB + OFF_MISC + 8)), inv = __uint_as_float(lds32(SB + OFF_MISC + 12));
        const float g0 = bf16r(((__uint_as_float(p0.x) + __uint_as_float(p2.x)) - mean * (__uint_as_float(p0.z) + __uint_as_float(p2.z))) * inv);
        const float g1 = bf16r(((__uint_as_float(p0.y) + __uint_as_float(p2.y)) - mean * (__uint_as_float(p0.w) + __uint_as_float(p2.w))) * inv);
        const float u0v = bf16r(((__uint_as_float(p1.x) + __uint_as_float(p3.x)) - mean * (__uint_as_float(p1.z) + __uint_as_float(p3.z))) * inv);
        const float u1v = bf16r(((__uint_as_float(p1.y) + __uint_as_float(p3.y)) - mean * (__uint_as_float(p1.w) + __uint_as_float(p3.w))) * inv);
        const float s0 = bf16r(__fdividef(1.f, 1.f + __expf(-g0))), s1 = bf16r(__fdividef(1.f, 1.f + __expf(-g1)));
        const uint32_t hw = pack2(s0 * u0v, s1 * u1v);
        uint32_t a[8];
#pragma unroll
        for (int k = 0; k < 8; k++) a[k] = __shfl_sync(~0u, hw, k * 4 + t);
        float c0[4] = {}, c1[4] = {}, c2[4] = {}, c3[4] = {};
        mma16816(c0, a[0], 0, a[4], 0, b[0][0], b[0][1]);
        mma16816(c1, a[0], 0, a[4], 0, b[2][0], b[2][1]);
        mma16816(c2, a[1], 0, a[5], 0, b[0][2], b[0][3]);
        mma16816(c3, a[1], 0, a[5], 0, b[2][2], b[2][3]);
        mma16816(c0, a[2], 0, a[6], 0, b[1][0], b[1][1]);
        mma16816(c1, a[2], 0, a[6], 0, b[3][0], b[3][1]);
        mma16816(c2, a[3], 0, a[7], 0, b[1][2], b[1][3]);
        mma16816(c3, a[3], 0, a[7], 0, b[3][2], b[3][3]);
        if (a6) mb_put2f(mb + o6, (g & 1) ? c1[0] + c3[0] : c0[0] + c2[0], (g & 1) ? c1[1] + c3[1] : c0[1] + c2[1]);
    }
    asm volatile("bar.arrive 12, 288;" ::: "memory");
    if (tid == 0) TRACE(12);
}

__device__ float f_q[4096], f_qa[16 * 1024], f_s[16 * 8192], f_cc[64 * 16 * 1024], f_ctx[4096], f_h[448], f_hh[1792];

__device__ __forceinline__ void block_ln(const float* v  , float* o  ) {
    float a[14];
    const int lane = threadIdx.x & 31;
#pragma unroll
    for (int i = 0; i < 14; i++) a[i] = v[lane + 32 * i];
    float mb, den;
    ln_stats(a, mb, den);
    for (int i = threadIdx.x; i < 448; i += blockDim.x) o[i] = bf16r(ln_apply(v[i], mb, den));
    __syncthreads();
}
__global__ void fb_q(const __nv_bfloat16* x, const __nv_bfloat16* wq) {
    __shared__ float xs[448], xn[448];
    for (int i = threadIdx.x; i < 448; i += blockDim.x) xs[i] = __bfloat162float(x[i]);
    __syncthreads();
    block_ln(xs, xn);
    const int c = blockIdx.x * blockDim.x + threadIdx.x;
    float a = 0.f;
    for (int m = 0; m < 448; m++) a += xn[m] * __bfloat162float(wq[(size_t)m * 4096 + c]);
    f_q[c] = bf16r(a);
}
__global__ void fb_qabs(const __nv_bfloat16* wuk) {
    const int row = blockIdx.x * 8 + (threadIdx.x >> 5), lane = threadIdx.x & 31;
    const int h = row & 15, c = row >> 4;
    float a = 0.f;
    for (int d = lane; d < 256; d += 32) a += f_q[h * 256 + d] * __bfloat162float(wuk[(size_t)row * 256 + d]);
    for (int o = 16; o; o >>= 1) a += __shfl_xor_sync(~0u, a, o);
    if (lane == 0) f_qa[h * 1024 + c] = a * 0.0625f;
}
__global__ void fb_scores(const __nv_bfloat16* ckv) {
    const int k = blockIdx.x * 8 + (threadIdx.x >> 5), lane = threadIdx.x & 31;
    float a[16] = {};
    for (int c = lane; c < 1024; c += 32) {
        const float v = __bfloat162float(ckv[(size_t)k * 1024 + c]);
#pragma unroll
        for (int h = 0; h < 16; h++) a[h] += v * f_qa[h * 1024 + c];
    }
#pragma unroll
    for (int h = 0; h < 16; h++) {
        for (int o = 16; o; o >>= 1) a[h] += __shfl_xor_sync(~0u, a[h], o);
        if (lane == 0) f_s[h * 8192 + k] = a[h];
    }
}
__global__ void fb_softmax() {
    __shared__ float red[32];
    float* s = f_s + blockIdx.x * 8192;
    float m = -INFINITY;
    for (int i = threadIdx.x; i < 8192; i += blockDim.x) m = fmaxf(m, s[i]);
    for (int o = 16; o; o >>= 1) m = fmaxf(m, __shfl_xor_sync(~0u, m, o));
    if ((threadIdx.x & 31) == 0) red[threadIdx.x >> 5] = m;
    __syncthreads();
    m = red[0];
    for (int i = 1; i < (int)(blockDim.x >> 5); i++) m = fmaxf(m, red[i]);
    __syncthreads();
    float l = 0.f;
    for (int i = threadIdx.x; i < 8192; i += blockDim.x) { const float e = __expf(s[i] - m); s[i] = e; l += e; }
    for (int o = 16; o; o >>= 1) l += __shfl_xor_sync(~0u, l, o);
    if ((threadIdx.x & 31) == 0) red[threadIdx.x >> 5] = l;
    __syncthreads();
    l = 0.f;
    for (int i = 0; i < (int)(blockDim.x >> 5); i++) l += red[i];
    const float inv = 1.f / l;
    for (int i = threadIdx.x; i < 8192; i += blockDim.x) s[i] *= inv;
}
__global__ void fb_pv(const __nv_bfloat16* ckv) {
    const int c = blockIdx.y * 256 + threadIdx.x, kb = blockIdx.x * 128;
    float a[16] = {};
    for (int k = kb; k < kb + 128; k++) {
        const float v = __bfloat162float(ckv[(size_t)k * 1024 + c]);
#pragma unroll
        for (int h = 0; h < 16; h++) a[h] += v * f_s[h * 8192 + k];
    }
#pragma unroll
    for (int h = 0; h < 16; h++) f_cc[(blockIdx.x * 16 + h) * 1024 + c] = a[h];
}
__global__ void fb_ctx(const __nv_bfloat16* wuv) {
    __shared__ float cc[1024];
    const int h = blockIdx.x;
    for (int c = threadIdx.x; c < 1024; c += 256) {
        float a = 0.f;
        for (int i = 0; i < 64; i++) a += f_cc[(i * 16 + h) * 1024 + c];
        cc[c] = a;
    }
    __syncthreads();
    float a = 0.f;
    for (int c = 0; c < 1024; c++) a += cc[c] * __bfloat162float(wuv[(size_t)c * 4096 + h * 256 + threadIdx.x]);
    f_ctx[h * 256 + threadIdx.x] = bf16r(a);
}
__global__ void fb_o(const __nv_bfloat16* x, const __nv_bfloat16* wo) {
    __shared__ float red[8][32];
    const int m = blockIdx.x * 32 + (threadIdx.x & 31), p = threadIdx.x >> 5;
    float a = 0.f;
    for (int i = p * 512; i < p * 512 + 512; i++) a += f_ctx[i] * __bfloat162float(wo[(size_t)i * 448 + m]);
    red[p][threadIdx.x & 31] = a;
    __syncthreads();
    if (p == 0) {
        for (int i = 1; i < 8; i++) a += red[i][threadIdx.x];
        f_h[m] = bf16r(__bfloat162float(x[m]) + bf16r(a));
    }
}
__global__ void fb_gu(const __nv_bfloat16* wg, const __nv_bfloat16* wu) {
    __shared__ float hs[448], hn[448];
    for (int i = threadIdx.x; i < 448; i += blockDim.x) hs[i] = f_h[i];
    __syncthreads();
    block_ln(hs, hn);
    const int f = blockIdx.x * 64 + threadIdx.x;
    float a = 0.f, b = 0.f;
    for (int m = 0; m < 448; m++) {
        a += hn[m] * __bfloat162float(wg[(size_t)m * 1792 + f]);
        b += hn[m] * __bfloat162float(wu[(size_t)m * 1792 + f]);
    }
    f_hh[f] = bf16r(bf16r(1.f / (1.f + __expf(-bf16r(a)))) * bf16r(b));
}
__global__ void fb_down(const __nv_bfloat16* wd, __nv_bfloat16* out) {
    __shared__ float red[8][32];
    const int m = blockIdx.x * 32 + (threadIdx.x & 31), p = threadIdx.x >> 5;
    float a = 0.f;
    for (int i = p * 224; i < p * 224 + 224; i++) a += f_hh[i] * __bfloat162float(wd[(size_t)i * 448 + m]);
    red[p][threadIdx.x & 31] = a;
    __syncthreads();
    if (p == 0) {
        for (int i = 1; i < 8; i++) a += red[i][threadIdx.x];
        out[m] = __float2bfloat16_rn(f_h[m] + bf16r(a));
    }
}

typedef CUresult (*EncodeFn)(CUtensorMap*, CUtensorMapDataType, cuuint32_t, void*, const cuuint64_t*, const cuuint64_t*,
                             const cuuint32_t*, const cuuint32_t*, CUtensorMapInterleave, CUtensorMapSwizzle,
                             CUtensorMapL2promotion, CUtensorMapFloatOOBfill);

bool encode3(EncodeFn enc, CUtensorMap* m, const void* p, uint64_t rows, uint64_t rowbytes) {
    cuuint64_t dim[3] = {64, rows, rowbytes / 128};
    cuuint64_t str[2] = {rowbytes, 128};
    cuuint32_t box[3] = {64, 16, 4}, es[3] = {1, 1, 1};
    return enc(m, CU_TENSOR_MAP_DATA_TYPE_BFLOAT16, 3, const_cast<void*>(p), dim, str, box, es, CU_TENSOR_MAP_INTERLEAVE_NONE,
               CU_TENSOR_MAP_SWIZZLE_128B, CU_TENSOR_MAP_L2_PROMOTION_NONE, CU_TENSOR_MAP_FLOAT_OOB_FILL_NONE) == CUDA_SUCCESS;
}
bool encode2(EncodeFn enc, CUtensorMap* m, const void* p, uint64_t rows, uint64_t cols, uint32_t boxrows) {
    cuuint64_t dim[2] = {cols, rows};
    cuuint64_t str[1] = {cols * 2};
    cuuint32_t box[2] = {64, boxrows}, es[2] = {1, 1};
    return enc(m, CU_TENSOR_MAP_DATA_TYPE_BFLOAT16, 2, const_cast<void*>(p), dim, str, box, es, CU_TENSOR_MAP_INTERLEAVE_NONE,
               CU_TENSOR_MAP_SWIZZLE_128B, CU_TENSOR_MAP_L2_PROMOTION_NONE, CU_TENSOR_MAP_FLOAT_OOB_FILL_NONE) == CUDA_SUCCESS;
}

int g_force_fallback = 0;
int g_force_nc = 0;
int g_window = 0x2233;
unsigned g_dly = (24u << 10) | (8u << 15);

}

extern "C" void kernel_launch(void* const* d_in, const int* in_sizes, int n_in, void* d_out, int out_size) {
    const __nv_bfloat16* x = (const __nv_bfloat16*)d_in[0];
    const __nv_bfloat16* ckv = (const __nv_bfloat16*)d_in[1];
    const __nv_bfloat16* wq = (const __nv_bfloat16*)d_in[2];
    const __nv_bfloat16* wuk = (const __nv_bfloat16*)d_in[3];
    const __nv_bfloat16* wuv = (const __nv_bfloat16*)d_in[4];
    const __nv_bfloat16* wo = (const __nv_bfloat16*)d_in[5];
    const __nv_bfloat16* wg = (const __nv_bfloat16*)d_in[7];
    const __nv_bfloat16* wu = (const __nv_bfloat16*)d_in[8];
    const __nv_bfloat16* wd = (const __nv_bfloat16*)d_in[9];
    __nv_bfloat16* out = (__nv_bfloat16*)d_out;
    cudaStream_t st = cudaStreamPerThread;

    static int s_init = 0, s_nc = 0;
    static EncodeFn s_enc = nullptr;
    cudaLaunchConfig_t cfg = {};
    cudaLaunchAttribute at[1];
    at[0].id = cudaLaunchAttributeClusterDimension;
    at[0].val.clusterDim.x = 4; at[0].val.clusterDim.y = 1; at[0].val.clusterDim.z = 1;
    cfg.blockDim = dim3(NTHR); cfg.dynamicSmemBytes = SMEM_BYTES + 128; cfg.stream = st; cfg.attrs = at; cfg.numAttrs = 1;
    if (!s_init) {
        s_init = 1;
        void* fn = nullptr;
        cudaDriverEntryPointQueryResult qr;
        if (cudaGetDriverEntryPoint("cuTensorMapEncodeTiled", &fn, cudaEnableDefault, &qr) == cudaSuccess &&
            qr == cudaDriverEntryPointSuccess)
            s_enc = (EncodeFn)fn;
        int nc = 0;
        cfg.gridDim = dim3(4 * NC_MAX);
        if (cudaFuncSetAttribute(fused_kernel, cudaFuncAttributeMaxDynamicSharedMemorySize, SMEM_BYTES + 128) == cudaSuccess &&
            cudaOccupancyMaxActiveClusters(&nc, fused_kernel, &cfg) == cudaSuccess)
            s_nc = nc > NC_MAX ? NC_MAX : nc;
        (void)cudaGetLastError();
    }
    if (g_force_nc && g_force_nc < s_nc) s_nc = g_force_nc;
    Params P;
    bool ok = s_enc != nullptr && s_nc >= NC_MIN && !g_force_fallback;
    ok = ok && encode3(s_enc, &P.wq, wq, 448, 8192) && encode3(s_enc, &P.wuk, wuk, 1024, 8192) &&
         encode3(s_enc, &P.ckv, ckv, 8192, 2048) && encode3(s_enc, &P.wuv, wuv, 1024, 8192) &&
         encode2(s_enc, &P.wo, wo, 4096, 448, 64) && encode2(s_enc, &P.wg, wg, 448, 1792, 112) &&
         encode2(s_enc, &P.wu, wu, 448, 1792, 112) && encode2(s_enc, &P.wd, wd, 1792, 448, 64);
    if (ok) {
        P.x = x; P.out = out; P.NC = s_nc; P.W = g_window; P.dly = g_dly;
        const int N = 4 * s_nc;
        int ustart[4 * NC_MAX + 1], kstart[NC_MAX + 1];
        {
            const int kbase = 512 / s_nc, kext = 512 - kbase * s_nc;
            kstart[0] = 0;
            for (int jj = 0; jj < s_nc; jj++) kstart[jj + 1] = kstart[jj] + kbase + (jj >= s_nc - kext ? 1 : 0);
            int cap = 0;
            for (int c = 0; c < N; c++) cap += (kstart[(c >> 2) + 1] - kstart[c >> 2] > 17) ? 8 : 9;
            const bool deep = cap >= 1024;
            P.RS = deep ? 5 : 3;
            int nine = 0;
            for (int c = 0; c < N; c++) nine += (!deep || kstart[(c >> 2) + 1] - kstart[c >> 2] <= 17) ? 1 : 0;
            const int uext = 1024 - 8 * N;
            ustart[0] = 0;
            for (int c = 0, i = 0; c < N; c++) {
                int extra = 0;
                if (!deep || kstart[(c >> 2) + 1] - kstart[c >> 2] <= 17) { extra = (i + 1) * uext / nine - i * uext / nine; i++; }
                ustart[c + 1] = ustart[c] + 8 + extra;
            }
        }
        auto owner = [&](int u) { int c = 0; while (ustart[c + 1] <= u) c++; return c; };
        for (int c = 0; c < 4 * NC_MAX; c++) {
            if (c >= N) { P.tab[c] = make_uint2(0, 0); continue; }
            const int jj = c >> 2, u0 = ustart[c], nu = ustart[c + 1] - u0;
            const int k0 = kstart[jj], nk = kstart[jj + 1] - k0;
            const int h7 = (c / 7) & 15, mb7 = c % 7, hA = u0 >> 6, hB = (u0 + nu - 1) >> 6;
            const int ns = owner(h7 * 64 + 63) - owner(h7 * 64) + 1;
            P.tab[c].x = u0 | (nu << 10) | (k0 << 14) | (nk << 23);
            P.tab[c].y = h7 | (mb7 << 4) | ((c - owner(hA * 64)) << 8) | ((c - owner(hB * 64)) << 12) | (ns << 16);
        }
        cfg.gridDim = dim3(4 * s_nc);
        cudaLaunchKernelEx(&cfg, fused_kernel, P);
        return;
    }
    fb_q<<<16, 256, 0, st>>>(x, wq);
    fb_qabs<<<2048, 256, 0, st>>>(wuk);
    fb_scores<<<1024, 256, 0, st>>>(ckv);
    fb_softmax<<<16, 1024, 0, st>>>();
    fb_pv<<<dim3(64, 4), 256, 0, st>>>(ckv);
    fb_ctx<<<16, 256, 0, st>>>(wuv);
    fb_o<<<14, 256, 0, st>>>(x, wo);
    fb_gu<<<28, 64, 0, st>>>(wg, wu);
    fb_down<<<14, 256, 0, st>>>(wd, out);
}
```

```cpp
#include <cuda_runtime.h>
#include <cuda_bf16.h>
#include <cuda.h>
#include <stdint.h>
#include <limits.h>

namespace {

constexpr int NC_MAX = 32, NC_MIN = 29;
constexpr int NTHR = 512;

constexpr uint32_t UNIT = 8192;
constexpr uint32_t OFF_CKV = 0;
constexpr uint32_t OFF_WA = 18 * UNIT;
constexpr uint32_t OFF_X = OFF_WA + 9 * UNIT;
constexpr uint32_t OFF_SLOT = OFF_X;
constexpr uint32_t OFF_PBUF = OFF_X + 3 * 2048;
constexpr uint32_t PSTRIDE = 1088;
constexpr uint32_t OFF_BAR = OFF_PBUF + 4 * PSTRIDE;
constexpr uint32_t OFF_MISC = OFF_BAR + 42 * 8;
constexpr uint32_t OFF_WGT = OFF_CKV + 10 * UNIT;
constexpr uint32_t OFF_REF = OFF_MISC + 16;
constexpr uint32_t OFF_PVC = OFF_REF + 48;
constexpr uint32_t SMEM_BYTES = OFF_PVC + 64;
constexpr uint32_t OFF_QST = OFF_PBUF;
constexpr uint32_t OFF_TILE = OFF_X;
constexpr uint32_t OFF_CTX = OFF_X + 9216;
constexpr uint32_t OFF_AFR = OFF_X + 9728;
constexpr uint32_t OFF_H = OFF_X;
constexpr uint32_t OFF_GU = OFF_X + 1024;
static_assert(OFF_AFR + 576 <= OFF_BAR, "staging overflow");
static_assert(SMEM_BYTES + 128 <= 232448, "smem overflow");

enum { B_S0 = 26, B_P0 = 31, B_H = 37, B_GU = 38, G_P1 = 39, G_QA = 40, NBARS = 41 };

struct __align__(64) Params {
    CUtensorMap wq, wuk, ckv, wuv, wo, wg, wu, wd;
    const __nv_bfloat16* x;
    __nv_bfloat16* out;
    int NC;
    int W;
    unsigned dly;
    int RS;
    uint2 tab[4 * NC_MAX];
};

constexpr uint32_t MB1 = 0;
constexpr uint32_t MB2 = MB1 + 112 * 1024;
constexpr uint32_t MB3 = MB2 + 32768;
constexpr uint32_t MBM = MB3 + 1024 * 1024;
constexpr uint32_t MB4 = MBM + 16384;
constexpr uint32_t MB5 = MB4 + 16 * 12 * 1024;
constexpr uint32_t MB6 = MB5 + 16 * 1792;
constexpr uint32_t MB_SET = (MB6 + 4 * 28 * 28 * 32 + 1023) / 1024 * 1024;
__device__ __align__(1024) unsigned char g_mb[2 * MB_SET];
__device__ unsigned g_epoch;
#define TRACE(i) do {} while (0)

constexpr int SPIN_LIMIT = 1 << 18;
__device__ __forceinline__ void mbar_init(uint32_t b, uint32_t c) {
    asm volatile("mbarrier.init.shared::cta.b64 [%0], %1;" ::"r"(b), "r"(c) : "memory");
}
__device__ __forceinline__ void mbar_expect(uint32_t b, uint32_t bytes) {
    asm volatile("mbarrier.arrive.expect_tx.shared::cta.b64 _, [%0], %1;" ::"r"(b), "r"(bytes) : "memory");
}
__device__ __forceinline__ void mbar_arrive(uint32_t b) {
    asm volatile("mbarrier.arrive.shared::cta.b64 _, [%0];" ::"r"(b) : "memory");
}
__device__ __forceinline__ bool mbar_try(uint32_t b, uint32_t ph) {
    uint32_t ok;
    asm volatile("{.reg .pred p; mbarrier.try_wait.parity.shared::cta.b64 p, [%1], %2; selp.u32 %0,1,0,p;}"
                 : "=r"(ok) : "r"(b), "r"(ph) : "memory");
    return ok;
}
__device__ __forceinline__ bool mbar_test(uint32_t b, uint32_t ph) {
    uint32_t ok;
    asm volatile("{.reg .pred p; mbarrier.test_wait.parity.shared::cta.b64 p, [%1], %2; selp.u32 %0,1,0,p;}"
                 : "=r"(ok) : "r"(b), "r"(ph) : "memory");
    return ok;
}
__device__ __forceinline__ void mbar_wait(uint32_t b, uint32_t ph) {
#pragma unroll 1
    for (int i = 0; i < SPIN_LIMIT; i++)
        if (mbar_try(b, ph)) return;
}
__device__ __forceinline__ void mbar_wait_cl(uint32_t b, uint32_t ph) {
#pragma unroll 1
    for (int i = 0; i < SPIN_LIMIT; i++) {
        uint32_t ok;
        asm volatile("{.reg .pred p; mbarrier.try_wait.parity.acquire.cluster.shared::cta.b64 p, [%1], %2; selp.u32 %0,1,0,p;}"
                     : "=r"(ok) : "r"(b), "r"(ph) : "memory");
        if (ok) return;
    }
}
__device__ __forceinline__ void tma2p(uint32_t dst, const CUtensorMap* m, int x, int y, uint32_t bar, unsigned long long pol) {
    asm volatile("cp.async.bulk.tensor.2d.shared::cluster.global.mbarrier::complete_tx::bytes.L2::cache_hint [%0], [%1, {%3, %4}], [%2], %5;"
                 ::"r"(dst), "l"(m), "r"(bar), "r"(x), "r"(y), "l"(pol) : "memory");
}
__device__ __forceinline__ void tma3p(uint32_t dst, const CUtensorMap* m, int x, int y, int z, uint32_t bar, unsigned long long pol) {
    asm volatile("cp.async.bulk.tensor.3d.shared::cluster.global.mbarrier::complete_tx::bytes.L2::cache_hint [%0], [%1, {%3, %4, %5}], [%2], %6;"
                 ::"r"(dst), "l"(m), "r"(bar), "r"(x), "r"(y), "r"(z), "l"(pol) : "memory");
}
__device__ __forceinline__ uint32_t mapa(uint32_t a, uint32_t rank) {
    uint32_t r;
    asm("mapa.shared::cluster.u32 %0, %1, %2;" : "=r"(r) : "r"(a), "r"(rank));
    return r;
}
__device__ __forceinline__ void st_async_v4(uint32_t a, uint32_t x, uint32_t y, uint32_t z, uint32_t w, uint32_t bar) {
    asm volatile("st.async.weak.shared::cluster.mbarrier::complete_tx::bytes.v4.b32 [%0], {%1,%2,%3,%4}, [%5];"
                 ::"r"(a), "r"(x), "r"(y), "r"(z), "r"(w), "r"(bar) : "memory");
}
__device__ __forceinline__ void st_async_b32(uint32_t a, uint32_t x, uint32_t bar) {
    asm volatile("st.async.weak.shared::cluster.mbarrier::complete_tx::bytes.b32 [%0], %1, [%2];"
                 ::"r"(a), "r"(x), "r"(bar) : "memory");
}
__device__ __forceinline__ void ldsm4(uint32_t a, uint32_t& r0, uint32_t& r1, uint32_t& r2, uint32_t& r3) {
    asm volatile("ldmatrix.sync.aligned.m8n8.x4.shared.b16 {%0,%1,%2,%3}, [%4];"
                 : "=r"(r0), "=r"(r1), "=r"(r2), "=r"(r3) : "r"(a) : "memory");
}
__device__ __forceinline__ void ldsm4t(uint32_t a, uint32_t& r0, uint32_t& r1, uint32_t& r2, uint32_t& r3) {
    asm volatile("ldmatrix.sync.aligned.m8n8.x4.trans.shared.b16 {%0,%1,%2,%3}, [%4];"
                 : "=r"(r0), "=r"(r1), "=r"(r2), "=r"(r3) : "r"(a) : "memory");
}
__device__ __forceinline__ void mma16816(float (&c)[4], uint32_t a0, uint32_t a1, uint32_t a2, uint32_t a3, uint32_t b0, uint32_t b1) {
    asm("mma.sync.aligned.m16n8k16.row.col.f32.bf16.bf16.f32 {%0,%1,%2,%3}, {%4,%5,%6,%7}, {%8,%9}, {%0,%1,%2,%3};"
                 : "+f"(c[0]), "+f"(c[1]), "+f"(c[2]), "+f"(c[3]) : "r"(a0), "r"(a1), "r"(a2), "r"(a3), "r"(b0), "r"(b1));
}
__device__ __forceinline__ uint4 lds128(uint32_t a) {
    uint4 v;
    asm volatile("ld.shared.v4.u32 {%0,%1,%2,%3}, [%4];" : "=r"(v.x), "=r"(v.y), "=r"(v.z), "=r"(v.w) : "r"(a) : "memory");
    return v;
}
__device__ __forceinline__ uint32_t lds32(uint32_t a) {
    uint32_t v;
    asm volatile("ld.shared.u32 %0, [%1];" : "=r"(v) : "r"(a) : "memory");
    return v;
}
__device__ __forceinline__ uint32_t lds32_acq(uint32_t a) {
    uint32_t v;
    asm volatile("ld.acquire.cta.shared.u32 %0, [%1];" : "=r"(v) : "r"(a) : "memory");
    return v;
}
__device__ __forceinline__ uint4 lds128_vol(uint32_t a) {
    uint4 v;
    asm volatile("ld.volatile.shared.v4.u32 {%0,%1,%2,%3}, [%4];" : "=r"(v.x), "=r"(v.y), "=r"(v.z), "=r"(v.w) : "r"(a) : "memory");
    return v;
}
__device__ __forceinline__ void sts128_vol(uint32_t a, uint4 v) {
    asm volatile("st.volatile.shared.v4.u32 [%0], {%1,%2,%3,%4};" ::"r"(a), "r"(v.x), "r"(v.y), "r"(v.z), "r"(v.w) : "memory");
}
__device__ __forceinline__ void red_add_rel(uint32_t a, uint32_t v) {
    asm volatile("red.release.cta.shared.add.u32 [%0], %1;" ::"r"(a), "r"(v) : "memory");
}
__device__ __forceinline__ void pv_wait(uint32_t pvc, int k) {
#pragma unroll 1
    for (int it = 0; it < SPIN_LIMIT * 8; it++)
        if ((int)lds32_acq(pvc + k * 4) >= 8) return;
}
__device__ __forceinline__ void sts128(uint32_t a, uint4 v) {
    asm volatile("st.shared.v4.u32 [%0], {%1,%2,%3,%4};" ::"r"(a), "r"(v.x), "r"(v.y), "r"(v.z), "r"(v.w) : "memory");
}
__device__ __forceinline__ void sts32(uint32_t a, uint32_t v) {
    asm volatile("st.shared.u32 [%0], %1;" ::"r"(a), "r"(v) : "memory");
}
__device__ __forceinline__ void sts16(uint32_t a, uint16_t v) {
    asm volatile("st.shared.u16 [%0], %1;" ::"r"(a), "h"(v) : "memory");
}
__device__ __forceinline__ void bar_sync(int id, int n) {
    asm volatile("bar.sync %0, %1;" ::"r"(id), "r"(n) : "memory");
}
__device__ __forceinline__ float bf16r(float v) { return __bfloat162float(__float2bfloat16_rn(v)); }
__device__ __forceinline__ uint32_t pack2(float lo, float hi) {
    __nv_bfloat162 t = __floats2bfloat162_rn(lo, hi);
    return *reinterpret_cast<uint32_t*>(&t);
}
__device__ __forceinline__ float bflo(uint32_t w) { return __uint_as_float(w << 16); }
__device__ __forceinline__ float bfhi(uint32_t w) { return __uint_as_float(w & 0xffff0000u); }
__device__ __forceinline__ float ex2(float x) {
    float y;
    asm("ex2.approx.ftz.f32 %0, %1;" : "=f"(y) : "f"(x));
    return y;
}
__device__ __forceinline__ uint32_t ldg_early(const uint32_t* p) {
    uint32_t v;
    asm volatile("ld.global.nc.u32 %0, [%1];" : "=r"(v) : "l"(p));
    return v;
}

__device__ __forceinline__ void mb_st2(unsigned char* p, uint32_t a, uint32_t b) {
    asm volatile("st.relaxed.gpu.global.v2.u32 [%0], {%1,%2};" ::"l"(p), "r"(a), "r"(b) : "memory");
}
__device__ __forceinline__ void mb_put2(unsigned char* p, uint32_t a, uint32_t b) { mb_st2(p, a == 0u ? 0x80000000u : a, b); }
__device__ __forceinline__ void mb_put2f(unsigned char* p, float a, float b) { mb_put2(p, __float_as_uint(a), __float_as_uint(b)); }
__device__ __forceinline__ void mb_clear2(uint32_t off) {
    mb_st2(g_mb + off, 0u, 0u);
    mb_st2(g_mb + MB_SET + off, 0u, 0u);
}
__device__ __forceinline__ uint4 mb_ld4(const unsigned char* p) {
    uint4 v;
    asm volatile("ld.relaxed.gpu.global.v4.u32 {%0,%1,%2,%3}, [%4];" : "=r"(v.x), "=r"(v.y), "=r"(v.z), "=r"(v.w) : "l"(p) : "memory");
    return v;
}
template <int N, int STRIDE>
__device__ __forceinline__ void mb_poll(const unsigned char* p, int n, uint4 (&v)[N]) {
#pragma unroll
    for (int i = 0; i < N; i++) v[i] = i < n ? mb_ld4(p + i * STRIDE) : make_uint4(0, 0, 0, 0);
#pragma unroll 1
    for (int it = 0; it < SPIN_LIMIT; it++) {
        uint32_t m = 0xffffffffu;
#pragma unroll
        for (int i = 0; i < N; i++)
            if (i < n) m = min(m, min(v[i].x, v[i].z));
        if (m != 0u) break;
#pragma unroll
        for (int i = 0; i < N; i++)
            if (i < n && (N > 4 || min(v[i].x, v[i].z) == 0u)) v[i] = mb_ld4(p + i * STRIDE);
    }
}
__device__ __forceinline__ void delay(uint32_t clks) {
    const uint32_t t0 = clock();
    while (clock() - t0 < clks) {}
}

template <int N, int STRIDE>
__device__ __forceinline__ void mb_first(const unsigned char* p, int n, uint4 (&v)[N]) {
#pragma unroll
    for (int i = 0; i < N; i++) v[i] = i < n ? mb_ld4(p + i * STRIDE) : make_uint4(0, 0, 0, 0);
}
__device__ __forceinline__ void ln_stats(const float (&v)[14], float& mb, float& den) {
    float s = 0.f;
#pragma unroll
    for (int i = 0; i < 14; i++) s += v[i];
#pragma unroll
    for (int o = 16; o; o >>= 1) s += __shfl_xor_sync(~0u, s, o);
    const float mean = s * (1.f / 448.f);
    float q = 0.f;
#pragma unroll
    for (int i = 0; i < 14; i++) { const float d = v[i] - mean; q += d * d; }
#pragma unroll
    for (int o = 16; o; o >>= 1) q += __shfl_xor_sync(~0u, q, o);
    mb = bf16r(mean);
    den = bf16r(__fsqrt_rn(bf16r(bf16r(q * (1.f / 448.f)) + 1e-5f)));
}
__device__ __forceinline__ void ln_stats1(const float (&v)[14], float c, float& mb, float& den) {
    float s0 = 0.f, s1 = 0.f, q0 = 0.f, q1 = 0.f;
#pragma unroll
    for (int i = 0; i < 7; i++) {
        const float d0 = v[2 * i] - c, d1 = v[2 * i + 1] - c;
        s0 += d0; s1 += d1; q0 += d0 * d0; q1 += d1 * d1;
    }
    float s = s0 + s1, q = q0 + q1;
#pragma unroll
    for (int o = 16; o; o >>= 1) { s += __shfl_xor_sync(~0u, s, o); q += __shfl_xor_sync(~0u, q, o); }
    const float md = s * (1.f / 448.f);
    mb = bf16r(c + md);
    den = bf16r(__fsqrt_rn(bf16r(bf16r(fmaxf(q * (1.f / 448.f) - md * md, 0.f)) + 1e-5f)));
}
__device__ __forceinline__ float ln_apply(float v, float mb, float den) { return __fdiv_rn(bf16r(v - mb), den); }
__device__ __forceinline__ float ln_apply_r(float v, float mb, float rden) { return bf16r(v - mb) * rden; }

__device__ __forceinline__ uint32_t frag_off(int w) {
    const int s = w >> 3, half = (w >> 2) & 1, t = w & 3;
    return (uint32_t)((((s >> 1) * 4 + t) * 4 + (s & 1) * 2 + half) * 4);
}
__device__ __forceinline__ int f2o(float f) { const int i = __float_as_int(f); return i ^ ((i >> 31) & 0x7fffffff); }
__device__ __forceinline__ float o2f(int i) { return __int_as_float(i ^ ((i >> 31) & 0x7fffffff)); }

__device__ __forceinline__ void combine_unit(uint32_t SB, const unsigned char* src, int n, uint4 (&v)[2], int ul, bool isA, int lane) {
#pragma unroll 1
    for (int it = 0; it < SPIN_LIMIT; it++) {
        uint32_t m = 0xffffffffu;
        if (n > 0) m = min(m, min(v[0].x, v[0].z));
        if (n > 1) m = min(m, min(v[1].x, v[1].z));
        if (m != 0u) break;
        if (n > 0 && min(v[0].x, v[0].z) == 0u) v[0] = mb_ld4(src);
        if (n > 1 && min(v[1].x, v[1].z) == 0u) v[1] = mb_ld4(src + 512);
    }
    const uint32_t tile = SB + OFF_TILE + ul * 1024, wgt = SB + OFF_WGT + (isA ? 0 : 128);
    sts128(tile + lane * 16, v[0]);
    sts128(tile + 512 + lane * 16, v[1]);
    bar_sync(2, 352);
    const int t = lane & 3;
    uint32_t b[8];
    const uint32_t ts = tile + ((lane & 7) + (lane & 8)) * 32 + (lane >> 4) * 16;
    ldsm4t(ts, b[0], b[1], b[2], b[3]);
    ldsm4t(ts + 512, b[4], b[5], b[6], b[7]);
    const uint4 w0 = lds128(wgt + t * 16), w1 = lds128(wgt + 64 + t * 16);
    float c0[4] = {}, c1[4] = {}, c2[4] = {}, c3[4] = {};
    mma16816(c0, w0.x, w0.y, w0.z, w0.w, b[0], b[1]);
    mma16816(c1, w0.x, w0.y, w0.z, w0.w, b[2], b[3]);
    mma16816(c2, w1.x, w1.y, w1.z, w1.w, b[4], b[5]);
    mma16816(c3, w1.x, w1.y, w1.z, w1.w, b[6], b[7]);
    const float v0 = (c0[0] + c0[2]) + (c2[0] + c2[2]), v1 = (c0[1] + c0[3]) + (c2[1] + c2[3]);
    const float v2 = (c1[0] + c1[2]) + (c3[0] + c3[2]), v3 = (c1[1] + c1[3]) + (c3[1] + c3[3]);
    const uint32_t a0 = pack2(v0, v1), a2 = pack2(v2, v3);
    const uint32_t a1 = pack2(v0 - bflo(a0), v1 - bfhi(a0)), a3 = pack2(v2 - bflo(a2), v3 - bfhi(a2));
    if (lane < 4) sts128(SB + OFF_AFR + ul * 64 + t * 16, make_uint4(a0, a1, a2, a3));
}

__global__ void __launch_bounds__(NTHR, 1) fused_kernel(const __grid_constant__ Params P) {
    extern __shared__ __align__(1024) unsigned char smem_raw[];
    const uint32_t SB = (uint32_t)__cvta_generic_to_shared(smem_raw);
    const int tid = threadIdx.x, warp = tid >> 5, lane = tid & 31;
    const int g = lane >> 2, t = lane & 3;
    const int cta = blockIdx.x, j = cta >> 2, r = cta & 3;
    const uint2 tab = P.tab[cta];
    const int u0 = tab.x & 1023, nu = (tab.x >> 10) & 15, k0 = (tab.x >> 14) & 511, nk = (tab.x >> 23) & 31;
    const int h7 = tab.y & 15, mb7 = (tab.y >> 4) & 7;
    const bool full = cta < 112;
    const int nb = (nk + 1) >> 1, nbg = nk >> 1;
    const int g_uk = full ? 2 : 0, g_kv = g_uk + 4, g_uv = g_kv + nbg, g_wo = g_uv + 4, g_gu = g_wo + 2, g_wd = g_gu + 2;
    auto BAR = [&](int i) -> uint32_t { return SB + OFF_BAR + 8 * i; };

    if (warp == 11) {
        const int W1 = P.W & 15, W2 = (P.W >> 4) & 15, W3 = (P.W >> 8) & 15, W4 = (P.W >> 12) & 15, ngroups = full ? g_wd + 1 : g_wo;
        int done = 0;
        unsigned long long pol;
        asm volatile("createpolicy.fractional.L2::evict_first.b64 %0, 1.0;" : "=l"(pol));
        if (lane < 8) asm volatile("prefetch.tensormap [%0];" ::"l"(reinterpret_cast<const char*>(&P) + lane * 128) : "memory");
        if (lane == 0) {
            mbar_init(BAR(0), 1);
            mbar_init(BAR(1), 1);
            mbar_init(BAR(2), 1);
            mbar_init(BAR(3), 1);
            asm volatile("fence.mbarrier_init.release.cluster;" ::: "memory");
        }
        __syncwarp();
#pragma unroll 1
        for (int gi = 0; gi < ngroups; gi++) {
            if (gi == min(W1, 4)) {
                __syncthreads();
                asm volatile("barrier.cluster.arrive.relaxed.aligned;" ::: "memory");
            }
            const CUtensorMap* map;
            uint32_t dst, dstep = UNIT;
            int n = 2, x0 = 0, y0, z0 = -1, x1 = 0, y1, z1 = 0, y2 = 0, z2 = 0, gate = -1, pvgate = 0;
            if (gi < g_uk) {
                map = &P.wq; dst = OFF_CKV + (14 + 2 * gi) * UNIT;
                y0 = mb7 * 64 + gi * 32; y1 = y0 + 16; z0 = z1 = h7 * 4;
            } else if (gi < g_kv || (gi >= g_uv && gi < g_wo)) {
                const bool uv = gi >= g_uv;
                const int i0 = 2 * (gi - (uv ? g_uv : g_uk)), u = u0 + i0;
                if (gi == g_uv) gate = G_QA;
                map = uv ? &P.wuv : &P.wuk; dst = OFF_WA + i0 * UNIT; n = i0 == 6 ? nu - 6 : 2;
                y0 = (u & 63) * 16; z0 = (u >> 6) * 4; y1 = ((u + 1) & 63) * 16; z1 = ((u + 1) >> 6) * 4;
                y2 = ((u + 2) & 63) * 16; z2 = ((u + 2) >> 6) * 4;
            } else if (gi < g_uv) {
                const int b = gi - g_kv;
                if (b == 7 && full) gate = G_P1;
                map = &P.ckv; dst = OFF_CKV + 2 * b * UNIT; n = b == nbg - 1 ? nk - 2 * b : 2;
                y0 = (k0 + 2 * b) * 16; y1 = y0 + 16; y2 = y0 + 32; z0 = z1 = z2 = r * 4;
            } else if (gi < g_gu) {
                const int i = gi - g_wo;
                pvgate = 1;
                map = &P.wo; dst = OFF_CKV + 2 * i * UNIT;
                x0 = x1 = mb7 * 64; y0 = h7 * 256 + i * 128; y1 = y0 + 64;
            } else if (gi < g_wd) {
                const int i = gi - g_gu;
                pvgate = 3;
                map = (r & 1) ? &P.wu : &P.wg; dst = OFF_CKV + 4 * UNIT + i * 14336; n = 1; dstep = 14336;
                x0 = j * 64; y0 = (r >> 1) * 224 + i * 112; y1 = 0;
            } else {
                pvgate = 4;
                map = &P.wd; dst = OFF_CKV + 8 * UNIT;
                x0 = r * 112; x1 = x0 + 64; y0 = y1 = j * 64;
            }
            if (gate >= 0) mbar_wait(BAR(gate), 0);
            if (pvgate) pv_wait(SB + OFF_PVC, pvgate);
            {
                const int W = gi < g_kv ? W1 : gi < g_uv ? W2 : gi < g_wo ? W3 : W4;
#pragma unroll 1
                for (; done <= gi - W; done++) mbar_wait(BAR(done), 0);
            }
            if (lane == 0) {
                const uint32_t bar = BAR(gi);
                mbar_expect(bar, n * dstep);
                if (z0 >= 0) {
                    tma3p(SB + dst, map, 0, y0, z0, bar, pol);
                    tma3p(SB + dst + UNIT, map, 0, y1, z1, bar, pol);
                    if (n > 2) tma3p(SB + dst + 2 * UNIT, map, 0, y2, z2, bar, pol);
                } else {
                    tma2p(SB + dst, map, x0, y0, bar, pol);
                    if (n > 1) tma2p(SB + dst + UNIT, map, x1, y1, bar, pol);
                }
                if (gi == g_kv) TRACE(15);
                if (gi == g_uv) TRACE(19);
                if (gi == g_wo) TRACE(20);
            }
            __syncwarp();
        }
        if (lane == 0) TRACE(31);
        asm volatile("barrier.cluster.wait.acquire.aligned;" ::: "memory");
        return;
    }

    uint32_t epoch, xr[7], xa[8], xw0, xw1;
    {
        const uint32_t* x32 = reinterpret_cast<const uint32_t*>(P.x);
        asm volatile("ld.relaxed.gpu.global.u32 %0, [%1];" : "=r"(epoch) : "l"(&g_epoch) : "memory");
#pragma unroll
        for (int i = 0; i < 7; i++) xr[i] = ldg_early(x32 + lane + 32 * i);
#pragma unroll
        for (int i = 0; i < 8; i++) xa[i] = ldg_early(x32 + mb7 * 32 + (i >> 1) * 8 + (i & 1) * 4 + t);
        xw0 = ldg_early(x32 + r * 56 + 2 * min(lane, 27));
        xw1 = ldg_early(x32 + r * 56 + 2 * min(lane, 27) + 1);
    }
    if (lane == 0) {
#pragma unroll 1
        for (int i = 4 + (warp > 11 ? warp - 1 : warp); i < NBARS; i += 15) mbar_init(BAR(i), i == G_P1 ? 8 : i == G_QA ? 4 : i == B_GU ? 2 : 1);
        if (warp >= 8 && warp < 11) sts128(SB + OFF_REF + (warp - 8) * 16, make_uint4(0, 0, 0, 0));
        if (warp >= 12) sts128(SB + OFF_PVC + (warp - 12) * 16, make_uint4(0, 0, 0, 0));
        asm volatile("fence.mbarrier_init.release.cluster;" ::: "memory");
    }
    __syncthreads();
    asm volatile("barrier.cluster.arrive.relaxed.aligned;" ::: "memory");
    const int NC = P.NC;
    const int hA = u0 >> 6, hB = (u0 + nu - 1) >> 6;
    const int RS = P.RS, RP = RS + 1;
    const uint32_t xoff = nk <= 17 ? OFF_CKV + 17 * UNIT : OFF_WA + 8 * UNIT;
    auto slot_off = [&](int i) -> uint32_t { return i < 3 ? OFF_SLOT + i * 2048 : xoff + (i - 3) * 2048; };
    auto p_off = [&](int i) -> uint32_t { return i < 4 ? OFF_PBUF + i * PSTRIDE : xoff + 4096 + (i - 4) * PSTRIDE; };

    if (warp >= 12) {
        const int nt = warp - 12;
        const uint32_t s_dst = mapa(SB + r * 512 + (nt * 2 + (g >> 2)) * 64 + t * 16, g & 3);
        const uint32_t s_bar = mapa(BAR(B_S0), g & 3);
        const int srow = (nt & 1) * 8 + (lane & 7);
        const uint32_t s_src0 = SB + OFF_CKV + (nt >> 1) * UNIT + srow * 128 + (((lane >> 3) ^ (srow & 7)) << 4);
        const uint32_t s_src1 = SB + OFF_CKV + (nt >> 1) * UNIT + srow * 128 + (((4 + (lane >> 3)) ^ (srow & 7)) << 4);
        unsigned char* const mb = g_mb + (epoch & 1) * MB_SET;
        const int ht = tid - 384;
        bar_sync(13, 384);
        delay((P.dly & 31) * 64);
        if (ht < 64 || hB != hA) {
            const int i = ht & 63, hs = ht >> 6;
            uint4 v[7];
            mb_poll<7, 1024>(mb + MB1 + (hs ? hB : hA) * 7168 + i * 16, 7, v);
            float a0 = 0.f, a1 = 0.f, a2 = 0.f, a3 = 0.f;
#pragma unroll
            for (int k = 0; k < 7; k++) {
                a0 += __uint_as_float(v[k].x); a1 += __uint_as_float(v[k].y);
                a2 += __uint_as_float(v[k].z); a3 += __uint_as_float(v[k].w);
            }
            const uint32_t d = SB + OFF_QST + hs * 512 + frag_off(2 * i);
            sts32(d, pack2(a0, a1));
            sts32(d + 16, pack2(a2, a3));
        }
        asm volatile("bar.arrive 7, 384;" ::: "memory");
        asm volatile("barrier.cluster.wait.acquire.aligned;" ::: "memory");
        {
            bar_sync(6, 384);
            delay(((P.dly >> 5) & 31) * 64);
            uint4 v[4];
            mb_poll<4, 2048>(mb + MB2 + r * 8192 + ht * 16, 4, v);
            const uint32_t a = SB + OFF_WA + ((ht >> 1) & 15) * 512 + ((ht >> 5) * 4 + (ht & 1) * 2) * 16;
            sts128(a, make_uint4(v[0].x, v[2].x, v[0].y, v[2].y));
            sts128(a + 16, make_uint4(v[0].z, v[2].z, v[0].w, v[2].w));
            sts128(a + 256, make_uint4(v[1].x, v[3].x, v[1].y, v[3].y));
            sts128(a + 272, make_uint4(v[1].z, v[3].z, v[1].w, v[3].w));
            bar_sync(9, 128);
        }
        if (ht == 0) TRACE(4);
        uint32_t qa[16][4];
#pragma unroll
        for (int s = 0; s < 16; s++) {
            const uint4 q = lds128(SB + OFF_WA + s * 512 + lane * 16);
            qa[s][0] = q.x; qa[s][1] = q.y; qa[s][2] = q.z; qa[s][3] = q.w;
        }
        __syncwarp();
        if (lane == 0) mbar_arrive(BAR(G_QA));
        const int nbs = (nk - (nt >> 1) + 1) >> 1;
        int sb = 0;
        bool landed = false;
#pragma unroll 1
        for (int b = 0; b < nbs; b++) {
            if (!landed) mbar_wait(BAR(g_kv + b), 0);
            float c0[4] = {}, c1[4] = {}, c2[4] = {}, c3[4] = {};
#pragma unroll
            for (int i = 0; i < 4; i++) {
                uint32_t b0, b1, b2, b3, b4, b5, b6, b7;
                ldsm4(s_src0 + 2 * b * UNIT + i * 2048, b0, b1, b2, b3);
                ldsm4(s_src1 + 2 * b * UNIT + i * 2048, b4, b5, b6, b7);
                mma16816(c0, qa[4 * i][0], qa[4 * i][1], qa[4 * i][2], qa[4 * i][3], b0, b1);
                mma16816(c1, qa[4 * i + 1][0], qa[4 * i + 1][1], qa[4 * i + 1][2], qa[4 * i + 1][3], b2, b3);
                mma16816(c2, qa[4 * i + 2][0], qa[4 * i + 2][1], qa[4 * i + 2][2], qa[4 * i + 2][3], b4, b5);
                mma16816(c3, qa[4 * i + 3][0], qa[4 * i + 3][1], qa[4 * i + 3][2], qa[4 * i + 3][3], b6, b7);
            }
            landed = b + 1 >= nbg || mbar_test(BAR(g_kv + b + 1), 0);
            if (b >= RS) pv_wait(SB + OFF_PVC, b - RS);
            st_async_v4(s_dst + slot_off(sb), __float_as_uint((c0[0] + c1[0]) + (c2[0] + c3[0])),
                        __float_as_uint((c0[1] + c1[1]) + (c2[1] + c3[1])), __float_as_uint((c0[2] + c1[2]) + (c2[2] + c3[2])),
                        __float_as_uint((c0[3] + c1[3]) + (c2[3] + c3[3])), s_bar + sb * 8);
            if (++sb == RS) sb = 0;
        }
        if (!full) return;
        if (nt < 2) {
            bar_sync(10, 320);
            delay(((P.dly >> 15) & 31) * 64);
            uint4 v[10];
            mb_poll<10, 1024>(mb + MB4 + h7 * 12288 + ht * 16, (tab.y >> 16) & 15, v);
            float a0 = 0.f, a1 = 0.f, a2 = 0.f, a3 = 0.f, e0 = 0.f, e1 = 0.f, e2 = 0.f, e3 = 0.f;
#pragma unroll
            for (int k = 0; k < 5; k++) {
                a0 += __uint_as_float(v[k].x); a1 += __uint_as_float(v[k].y);
                a2 += __uint_as_float(v[k].z); a3 += __uint_as_float(v[k].w);
                e0 += __uint_as_float(v[5 + k].x); e1 += __uint_as_float(v[5 + k].y);
                e2 += __uint_as_float(v[5 + k].z); e3 += __uint_as_float(v[5 + k].w);
            }
            bar_sync(4, 96);
            const float rl = __uint_as_float(lds32(SB + OFF_MISC));
            const uint32_t d = SB + OFF_CTX + frag_off(2 * ht);
            sts32(d, pack2((a0 + e0) * rl, (a1 + e1) * rl));
            sts32(d + 16, pack2((a2 + e2) * rl, (a3 + e3) * rl));
            asm volatile("bar.arrive 8, 320;" ::: "memory");
        } else if (nt == 2) {
            bar_sync(11, 288);
            delay(((P.dly >> 20) & 31) * 64);
            if (lane < 28) {
                const int w = (r & 1) * 56 + 2 * lane;
                const uint32_t d0 = SB + OFF_H + (r >> 1) * 448 + frag_off(w);
                uint32_t da[4], ba[4];
#pragma unroll
                for (int k = 0; k < 4; k++) { da[k] = mapa(d0, k); ba[k] = mapa(BAR(B_H), k); }
                uint4 v[16];
                mb_poll<16, 1792>(mb + MB5 + r * 448 + lane * 16, 16, v);
                float a[4][4] = {};
#pragma unroll
                for (int k = 0; k < 16; k++) {
                    a[k & 3][0] += __uint_as_float(v[k].x); a[k & 3][1] += __uint_as_float(v[k].y);
                    a[k & 3][2] += __uint_as_float(v[k].z); a[k & 3][3] += __uint_as_float(v[k].w);
                }
                const uint32_t h0 = pack2(bflo(xw0) + bf16r((a[0][0] + a[1][0]) + (a[2][0] + a[3][0])),
                                          bfhi(xw0) + bf16r((a[0][1] + a[1][1]) + (a[2][1] + a[3][1])));
                const uint32_t h1 = pack2(bflo(xw1) + bf16r((a[0][2] + a[1][2]) + (a[2][2] + a[3][2])),
                                          bfhi(xw1) + bf16r((a[0][3] + a[1][3]) + (a[2][3] + a[3][3])));
#pragma unroll
                for (int k = 0; k < 4; k++) {
                    st_async_b32(da[k], h0, ba[k]);
                    st_async_b32(da[k] + 16, h1, ba[k]);
                }
            }
        } else {
            const int k = (lane >> 1) & 3;
            mbar_wait_cl(BAR(B_H), 0);
            {
                float v[14], mean, den;
#pragma unroll
                for (int i = 0; i < 7; i++) {
                    const uint32_t w = lds32(SB + OFF_H + (lane + 32 * i) * 4);
                    v[2 * i] = bflo(w); v[2 * i + 1] = bfhi(w);
                }
                ln_stats1(v, bflo(lds32(SB + OFF_H)), mean, den);
                if (lane == 0) {
                    sts32(SB + OFF_MISC + 8, __float_as_uint(mean));
                    sts32(SB + OFF_MISC + 12, __float_as_uint(__fdividef(1.f, den)));
                    mbar_arrive(BAR(B_GU));
                }
            }
            const uint32_t hw = lds32(SB + OFF_H + (r >> 1) * 448 + frag_off((r & 1) * 56 + j * 2 + (k >> 1)));
            uint4 v[4];
            const int n = lane < 4 ? 4 : lane < 8 ? 3 : 0;
            bar_sync(12, 288);
            delay(((P.dly >> 25) & 31) * 64);
            mb_poll<4, 256>(mb + MB6 + ((r * 28 + j) * 28 + lane) * 32, n, v);
            float v0 = (__uint_as_float(v[0].x) + __uint_as_float(v[1].x)) + (__uint_as_float(v[2].x) + __uint_as_float(v[3].x));
            float v1 = (__uint_as_float(v[0].y) + __uint_as_float(v[1].y)) + (__uint_as_float(v[2].y) + __uint_as_float(v[3].y));
            float v2 = (__uint_as_float(v[0].z) + __uint_as_float(v[1].z)) + (__uint_as_float(v[2].z) + __uint_as_float(v[3].z));
            float v3 = (__uint_as_float(v[0].w) + __uint_as_float(v[1].w)) + (__uint_as_float(v[2].w) + __uint_as_float(v[3].w));
            __syncwarp();
            const bool up = lane & 4;
            const float s0 = up ? v0 : v2, s1 = up ? v1 : v3;
            const float k0v = up ? v2 : v0, k1v = up ? v3 : v1;
            v0 = k0v + __shfl_xor_sync(~0u, s0, 4);
            v1 = k1v + __shfl_xor_sync(~0u, s1, 4);
            const bool up2 = lane & 2;
            const float s2 = up2 ? v0 : v1, k2v = up2 ? v1 : v0;
            v0 = k2v + __shfl_xor_sync(~0u, s2, 2);
            v0 += __shfl_xor_sync(~0u, v0, 1);
            if (lane < 8 && (lane & 1) == 0)
                P.out[r * 112 + j * 4 + k] = __float2bfloat16_rn(((k & 1) ? bfhi(hw) : bflo(hw)) + bf16r(v0));
            if (cta == 0 && lane == 0) g_epoch = epoch + 1;
            if (lane == 0) TRACE(13);
        }
        return;
    }
    if (warp >= 8) {
        const int sb = warp - 8, nt = lane >> 3, gg = (lane >> 2) & 1;
        if (lane == 0) {
            mbar_expect(BAR(B_S0 + sb), 2048);
            if (sb + 3 < RS) mbar_expect(BAR(B_S0 + sb + 3), 2048);
        }
        const uint32_t dst_a = mapa(SB + (nt >> 1) * 512 + ((r + 4 * gg) * 4 + t) * 16, (nt & 1) * 2);
        const uint32_t dst_b = mapa(SB + (nt >> 1) * 512 + ((r + 4 * gg) * 4 + t) * 16, (nt & 1) * 2 + 1);
        const uint32_t bar_a = mapa(BAR(B_P0), (nt & 1) * 2), bar_b = mapa(BAR(B_P0), (nt & 1) * 2 + 1);
        const uint32_t dst_m = mapa(SB + 1024 + (r + 4 * gg + 8 * nt) * 4, t), bar_m = mapa(BAR(B_P0), t);
        const uint32_t ref_prev = SB + OFF_REF + (sb == 0 ? 2 : sb - 1) * 16;
        asm volatile("barrier.cluster.wait.acquire.aligned;" ::: "memory");
#pragma unroll 1
        for (int b = sb; b < nb; b += 3) {
            const int si = b >= RS ? (b >= 2 * RS ? b - 2 * RS : b - RS) : b, sph = (b >= RS && b < 2 * RS) ? 1 : 0;
            const int pi = b >= RP ? (b >= 2 * RP ? b - 2 * RP : b - RP) : b;
            const uint32_t po = p_off(pi), bo = pi * 8, sa = SB + slot_off(si) + lane * 16;
            const bool valid = 2 * b + (nt >> 1) < nk;
            if (b >= RS) {
                const uint32_t tk = SB + OFF_REF + ((b - RS) % 3) * 16;
#pragma unroll 1
                for (int it = 0; it < SPIN_LIMIT * 8; it++)
                    if ((int)(lds128_vol(tk).x & 15u) > b - RS) break;
            }
            mbar_wait_cl(BAR(B_S0 + si), sph);
            if (lane == 0 && b == 5) TRACE(16);
            const uint4 v0 = lds128(sa), v1 = lds128(sa + 512), v2 = lds128(sa + 1024), v3 = lds128(sa + 1536);
            float s0 = (__uint_as_float(v0.x) + __uint_as_float(v1.x)) + (__uint_as_float(v2.x) + __uint_as_float(v3.x));
            float s1 = (__uint_as_float(v0.y) + __uint_as_float(v1.y)) + (__uint_as_float(v2.y) + __uint_as_float(v3.y));
            float s2 = (__uint_as_float(v0.z) + __uint_as_float(v1.z)) + (__uint_as_float(v2.z) + __uint_as_float(v3.z));
            float s3 = (__uint_as_float(v0.w) + __uint_as_float(v1.w)) + (__uint_as_float(v2.w) + __uint_as_float(v3.w));
            const int i0 = valid ? f2o(fmaxf(s0, s1)) : INT_MIN, i1 = valid ? f2o(fmaxf(s2, s3)) : INT_MIN;
            int ra = __reduce_max_sync(~0u, gg ? INT_MIN : i0), rb = __reduce_max_sync(~0u, gg ? i0 : INT_MIN);
            int rc = __reduce_max_sync(~0u, gg ? INT_MIN : i1), rd = __reduce_max_sync(~0u, gg ? i1 : INT_MIN);
            ra = (ra + 15) & ~15; rb = (rb + 15) & ~15; rc = (rc + 15) & ~15; rd = (rd + 15) & ~15;
            if (b > 0) {
                uint4 pr;
#pragma unroll 1
                for (int it = 0; it < SPIN_LIMIT * 8; it++) {
                    pr = lds128_vol(ref_prev);
                    if ((int)(pr.x & pr.y & pr.z & pr.w & 15u) == b && (int)((pr.x | pr.y | pr.z | pr.w) & 15u) == b) break;
                }
                ra = max(ra, (int)pr.x - b); rb = max(rb, (int)pr.y - b); rc = max(rc, (int)pr.z - b); rd = max(rd, (int)pr.w - b);
            }
            __syncwarp();
            if (lane == 0) sts128_vol(SB + OFF_REF + sb * 16, make_uint4(ra | (b + 1), rb | (b + 1), rc | (b + 1), rd | (b + 1)));
            const float n0 = o2f(gg ? rb : ra), n1 = o2f(gg ? rd : rc);
            const uint32_t w0 = pack2(ex2(s0 - n0), ex2(s1 - n0)), w1 = pack2(ex2(s2 - n1), ex2(s3 - n1));
            const uint32_t o0 = __shfl_xor_sync(~0u, w0, 8), o1 = __shfl_xor_sync(~0u, w1, 8);
            if (lane < 16) st_async_b32(dst_m + po, __float_as_uint(nt ? n1 : n0), bar_m + bo);
            if (valid) {
                const bool odd = nt & 1;
                const uint32_t x0 = odd ? o0 : w0, x1 = odd ? o1 : w1, x2 = odd ? w0 : o0, x3 = odd ? w1 : o1;
                st_async_v4(dst_a + po, x0, x1, x2, x3, bar_a + bo);
                st_async_v4(dst_b + po, x0, x1, x2, x3, bar_b + bo);
            }
            if (lane == 0 && b == 5) TRACE(17);
            if (lane == 0 && b + RS < nb) mbar_expect(BAR(B_S0 + si), (2 * (b + RS) + 1 < nk) ? 2048 : 1024);
        }
        bar_sync(5, 352);
        delay(((P.dly >> 10) & 31) * 64);
        const unsigned char* mbp = g_mb + (epoch & 1) * MB_SET;
        if (sb == 2) {
            const unsigned char* src = mbp + MB3 + (u0 + 8) * 1024 + lane * 16;
            const int n = nu > 8 ? ((16 + (lane >> 1) < NC) ? 2 : 1) : 0;
            uint4 v[2];
            mb_first<2, 512>(src, n, v);
            combine_unit(SB, src, n, v, 8, 8 < (hA + 1) * 64 - u0, lane);
            asm volatile("bar.arrive 3, 288;" ::: "memory");
        } else {
#pragma unroll 1
            for (int pass = 0; pass < ((sb == 0 && full) ? 2 : 1); pass++) {
                const unsigned char* pm = mbp + MBM + ((pass ? h7 : sb ? hB : hA) * NC_MAX + lane) * 32;
                uint2 a = make_uint2(0xff800000u, 0);
                if (lane < NC) {
#pragma unroll 1
                    for (int it = 0; it < SPIN_LIMIT; it++) {
                        asm volatile("ld.relaxed.gpu.global.v2.u32 {%0,%1}, [%2];" : "=r"(a.x), "=r"(a.y) : "l"(pm) : "memory");
                        if (a.x != 0u) break;
                    }
                }
                __syncwarp();
                const float mj = __uint_as_float(a.x);
                const float w = ex2(mj - o2f(__reduce_max_sync(~0u, f2o(mj))));
                if (pass == 0) {
                    const int jj = lane & 15;
                    const uint32_t d = SB + OFF_WGT + sb * 128 + ((lane >> 4) * 4 + ((jj & 7) >> 1)) * 16 + (jj >> 3) * 8 + (jj & 1) * 2;
                    const __nv_bfloat16 hi = __float2bfloat16_rn(w), lo = __float2bfloat16_rn(w - __bfloat162float(hi));
                    sts16(d, *reinterpret_cast<const uint16_t*>(&hi));
                    sts16(d + 4, *reinterpret_cast<const uint16_t*>(&lo));
                    asm volatile("bar.arrive 2, 352;" ::: "memory");
                } else {
                    float L = w * __uint_as_float(a.y);
#pragma unroll
                    for (int o = 16; o; o >>= 1) L += __shfl_xor_sync(~0u, L, o);
                    if (lane == 0) sts32(SB + OFF_MISC, __float_as_uint(__fdividef(1.f, L)));
                    asm volatile("bar.arrive 4, 96;" ::: "memory");
                }
            }
        }
        return;
    }

    if (tid == 0) {
#pragma unroll 1
        for (int i = 0; i < RP; i++) mbar_expect(BAR(B_P0 + i), 1088);
        mbar_expect(BAR(B_H), 896);
        mbar_expect(BAR(B_GU), 2048);
    }
    const uint32_t o1 = MB1 + cta * 1024 + warp * 128 + lane * 8;
    const uint32_t o3 = MB3 + ((g * 64 + r * 16 + warp * 2) * NC_MAX + j) * 32 + t * 8;
    const bool a4 = g < 4 || hB != hA;
    const uint32_t o4 = MB4 + ((g < 4 ? hA : hB) * 12 + ((tab.y >> (g < 4 ? 8 : 12)) & 15)) * 1024 + warp * 128 + (lane & 15) * 8;
    const uint32_t o5 = MB5 + h7 * 1792 + mb7 * 256 + warp * 32 + t * 8;
    const int li6 = (warp + 8 * (g & 1)) * 4 + t;
    const bool a6 = g < 4 && ((g & 1) == 0 || warp < 6);
    const uint32_t o6 = MB6 + ((r * 28 + (li6 >> 1)) * 28 + j) * 32 + (g >> 1) * 16 + (li6 & 1) * 8;
    const bool am = tid < 32 && (g & 3) == r;
    const uint32_t om = MBM + (g * NC_MAX + j) * 32 + t * 8;
    const int ua = u0 + warp, ub = u0 + 8;
    const uint32_t o2a = MB2 + ((((ua & 63) >> 4) * 16 + (ua >> 6)) * 16 + (ua & 15)) * 32 + (lane >> 3) * 8;
    const uint32_t o2b = MB2 + ((((ub & 63) >> 4) * 16 + (ub >> 6)) * 16 + (ub & 15)) * 32 + (lane >> 3) * 8;
    if (full && lane < 16) mb_clear2(o1);
    if ((lane & 7) == 0) {
        mb_clear2(o2a);
        if (warp == 0 && nu > 8) mb_clear2(o2b);
    }
    unsigned char* const mb = g_mb + (epoch & 1) * MB_SET;

    if (full) {
        float v[14];
#pragma unroll
        for (int i = 0; i < 7; i++) { v[2 * i] = bflo(xr[i]); v[2 * i + 1] = bfhi(xr[i]); }
        float mean, den;
        ln_stats(v, mean, den);
        const float rden = __frcp_rn(den);
#pragma unroll
        for (int i = 0; i < 8; i++) xa[i] = pack2(ln_apply_r(bflo(xa[i]), mean, rden), ln_apply_r(bfhi(xa[i]), mean, rden));
        if (tid == 0) TRACE(14);
        float acc[4][4] = {};
        const int row = (lane & 7) + (lane & 8), ch = (warp & 1) * 4 + (lane >> 4);
        const uint32_t a0 = SB + OFF_CKV + 14 * UNIT + (warp >> 1) * 2048 + row * 128;
#pragma unroll
        for (int s = 0; s < 4; s++) {
            if ((s & 1) == 0) mbar_wait(BAR(s >> 1), 0);
            uint32_t b0, b1, b2, b3, b4, b5, b6, b7;
            ldsm4t(a0 + s * UNIT + ((ch ^ (row & 7)) << 4), b0, b1, b2, b3);
            ldsm4t(a0 + s * UNIT + (((ch + 2) ^ (row & 7)) << 4), b4, b5, b6, b7);
            mma16816(acc[0], xa[2 * s], 0, xa[2 * s + 1], 0, b0, b1);
            mma16816(acc[1], xa[2 * s], 0, xa[2 * s + 1], 0, b2, b3);
            mma16816(acc[2], xa[2 * s], 0, xa[2 * s + 1], 0, b4, b5);
            mma16816(acc[3], xa[2 * s], 0, xa[2 * s + 1], 0, b6, b7);
        }
        const float v0 = (g & 2) ? ((g & 1) ? acc[3][0] : acc[2][0]) : ((g & 1) ? acc[1][0] : acc[0][0]);
        const float v1 = (g & 2) ? ((g & 1) ? acc[3][1] : acc[2][1]) : ((g & 1) ? acc[1][1] : acc[0][1]);
        if (lane < 16) mb_put2f(mb + o1, v0, v1);
        __syncwarp();
        if (lane == 0) mbar_arrive(BAR(G_P1));
    }
    asm volatile("bar.arrive 13, 384;" ::: "memory");
    if (tid == 0) TRACE(1);
    mb_clear2(o3); mb_clear2(o3 + 1024); mb_clear2(o3 + 524288); mb_clear2(o3 + 524288 + 1024);
    if (a4) mb_clear2(o4);
    if (am) { mb_clear2(om); mb_clear2(om + 8 * NC_MAX * 32); }
    if (full) {
        if (lane < 4) mb_clear2(o5);
        if (a6) mb_clear2(o6);
    }
    bar_sync(7, 384);
    if (tid == 0) TRACE(2);
    {
        const int row = (lane & 7) + (lane & 8), cs = lane >> 4;
        const float sc = 0.0625f * 1.4426950408889634f;
        {
            const uint32_t qs = SB + OFF_QST + ((ua >> 6) != hA ? 512 : 0) + t * 16;
            uint4 q[8];
#pragma unroll
            for (int s2 = 0; s2 < 8; s2++) q[s2] = lds128(qs + s2 * 64);
            mbar_wait(BAR(g_uk + (warp >> 1)), 0);
            float c[4][4] = {};
            const uint32_t a0 = SB + OFF_WA + warp * UNIT + row * 128;
#pragma unroll
            for (int s2 = 0; s2 < 8; s2++) {
                uint32_t r0, r1, r2, r3, r4, r5, r6, r7;
                ldsm4(a0 + (s2 >> 1) * 2048 + ((((s2 & 1) * 4 + cs) ^ (row & 7)) << 4), r0, r1, r2, r3);
                ldsm4(a0 + (s2 >> 1) * 2048 + ((((s2 & 1) * 4 + 2 + cs) ^ (row & 7)) << 4), r4, r5, r6, r7);
                mma16816(c[(s2 & 1) * 2], r0, r1, r2, r3, q[s2].x, q[s2].y);
                mma16816(c[(s2 & 1) * 2 + 1], r4, r5, r6, r7, q[s2].z, q[s2].w);
            }
            const float lo = ((c[0][0] + c[1][0]) + (c[2][0] + c[3][0])) * sc, hi = ((c[0][2] + c[1][2]) + (c[2][2] + c[3][2])) * sc;
            const float lo2 = __shfl_down_sync(~0u, lo, 4), hi2 = __shfl_down_sync(~0u, hi, 4);
            if ((lane & 7) == 0) mb_put2(mb + o2a, pack2(lo, lo2), pack2(hi, hi2));
        }
        if (nu > 8 && warp == 0) {
            const uint32_t qs = SB + OFF_QST + ((ub >> 6) != hA ? 512 : 0) + t * 16;
            uint4 q[8];
#pragma unroll
            for (int s2 = 0; s2 < 8; s2++) q[s2] = lds128(qs + s2 * 64);
            mbar_wait(BAR(g_uk + 3), 0);
            float c[4][4] = {};
            const uint32_t a0 = SB + OFF_WA + 8 * UNIT + row * 128;
#pragma unroll
            for (int s2 = 0; s2 < 8; s2++) {
                uint32_t r0, r1, r2, r3, r4, r5, r6, r7;
                ldsm4(a0 + (s2 >> 1) * 2048 + ((((s2 & 1) * 4 + cs) ^ (row & 7)) << 4), r0, r1, r2, r3);
                ldsm4(a0 + (s2 >> 1) * 2048 + ((((s2 & 1) * 4 + 2 + cs) ^ (row & 7)) << 4), r4, r5, r6, r7);
                mma16816(c[(s2 & 1) * 2], r0, r1, r2, r3, q[s2].x, q[s2].y);
                mma16816(c[(s2 & 1) * 2 + 1], r4, r5, r6, r7, q[s2].z, q[s2].w);
            }
            const float lo = ((c[0][0] + c[1][0]) + (c[2][0] + c[3][0])) * sc, hi = ((c[0][2] + c[1][2]) + (c[2][2] + c[3][2])) * sc;
            const float lo2 = __shfl_down_sync(~0u, lo, 4), hi2 = __shfl_down_sync(~0u, hi, 4);
            if ((lane & 7) == 0) mb_put2(mb + o2b, pack2(lo, lo2), pack2(hi, hi2));
        }
    }
    if (tid == 0) TRACE(3);
    asm volatile("bar.arrive 6, 384;" ::: "memory");
    asm volatile("barrier.cluster.wait.acquire.aligned;" ::: "memory");
    {
        float acc[4][4] = {};
        float mr0 = -INFINITY, mr1 = -INFINITY, tl[4] = {};
        const int prow = (lane & 7) + (lane & 8), pch = (warp & 1) * 4 + (lane >> 4);
        const uint32_t p_src0 = SB + OFF_CKV + (warp >> 1) * 2048 + prow * 128 + ((pch ^ (prow & 7)) << 4);
        const uint32_t p_src1 = SB + OFF_CKV + (warp >> 1) * 2048 + prow * 128 + (((pch + 2) ^ (prow & 7)) << 4);
        const uint32_t one = 0x3f803f80u;
#pragma unroll 1
        for (int b = 0, pb = 0, pph = 0; b < nb; b++) {
            const bool two = 2 * b + 1 < nk;
            const uint32_t pbase = SB + p_off(pb);
            mbar_wait_cl(BAR(B_P0 + pb), pph);
            if (tid == 0) TRACE(21 + b);
            uint32_t b0[8], b1[8];
            const float mb0 = __uint_as_float(lds32(pbase + 1024 + g * 4));
            const float mb1 = __uint_as_float(lds32(pbase + 1024 + 32 + g * 4));
            const uint4 p0 = lds128(pbase + lane * 16);
            ldsm4t(p_src0 + 2 * b * UNIT, b0[0], b0[1], b0[2], b0[3]);
            ldsm4t(p_src1 + 2 * b * UNIT, b0[4], b0[5], b0[6], b0[7]);
            uint4 p1;
            if (two) {
                p1 = lds128(pbase + 512 + lane * 16);
                ldsm4t(p_src0 + (2 * b + 1) * UNIT, b1[0], b1[1], b1[2], b1[3]);
                ldsm4t(p_src1 + (2 * b + 1) * UNIT, b1[4], b1[5], b1[6], b1[7]);
            }
            if (__any_sync(~0u, mb0 != mr0 || mb1 != mr1)) {
                const float al0 = ex2(mr0 - mb0), al1 = ex2(mr1 - mb1);
                mr0 = mb0; mr1 = mb1;
#pragma unroll
                for (int i = 0; i < 4; i++) { acc[i][0] *= al0; acc[i][1] *= al0; acc[i][2] *= al1; acc[i][3] *= al1; }
                tl[0] *= al0; tl[2] *= al1;
            }
#pragma unroll
            for (int i = 0; i < 4; i++) mma16816(acc[i], p0.x, p0.y, p0.z, p0.w, b0[2 * i], b0[2 * i + 1]);
            mma16816(tl, p0.x, p0.y, p0.z, p0.w, one, one);
            if (two) {
#pragma unroll
                for (int i = 0; i < 4; i++) mma16816(acc[i], p1.x, p1.y, p1.z, p1.w, b1[2 * i], b1[2 * i + 1]);
                mma16816(tl, p1.x, p1.y, p1.z, p1.w, one, one);
            }
            if (tid == 0 && b + RP < nb) mbar_expect(BAR(B_P0 + pb), (2 * (b + RP) + 1 < nk) ? 1088 : 576);
            __syncwarp();
            if (lane == 0) red_add_rel(SB + OFF_PVC + b * 4, 1);
            if (++pb == RP) { pb = 0; pph ^= 1; }
        }
        if (am) {
            mb_put2f(mb + om, mr0, tl[0]);
            mb_put2f(mb + om + 8 * NC_MAX * 32, mr1, tl[2]);
        }
        mb_put2(mb + o3, pack2(acc[0][0], acc[0][1]), pack2(acc[1][0], acc[1][1]));
        mb_put2(mb + o3 + 1024, pack2(acc[2][0], acc[2][1]), pack2(acc[3][0], acc[3][1]));
        mb_put2(mb + o3 + 524288, pack2(acc[0][2], acc[0][3]), pack2(acc[1][2], acc[1][3]));
        mb_put2(mb + o3 + 524288 + 1024, pack2(acc[2][2], acc[2][3]), pack2(acc[3][2], acc[3][3]));
    }
    if (tid == 0) TRACE(5);
    {
        const uint32_t tpub = clock();
        const unsigned char* psrc = mb + MB3 + ua * 1024 + lane * 16;
        const int pn = (16 + (lane >> 1) < NC) ? 2 : 1;
        bar_sync(5, 352);
        uint32_t wb[9][8];
        const int p = (lane & 7) + (lane & 8);
        const int prow = ((p >> 1) & 1) * 8 + (p >> 2) * 2 + (p & 1), pch = (warp & 1) * 4 + (lane >> 4);
        const uint32_t src0 = SB + OFF_WA + (warp >> 1) * 2048 + prow * 128 + ((pch ^ (prow & 7)) << 4);
        const uint32_t src1 = SB + OFF_WA + (warp >> 1) * 2048 + prow * 128 + (((pch + 2) ^ (prow & 7)) << 4);
        uint4 pv[2];
#pragma unroll
        for (int ul = 0; ul < 9; ul++) {
            const uint32_t uo = (ul < 8 || nu > 8) ? ul * UNIT : 0;
            if ((ul & 1) == 0 && ul < 8) mbar_wait(BAR(g_uv + (ul >> 1)), 0);
            ldsm4t(src0 + uo, wb[ul][0], wb[ul][1], wb[ul][2], wb[ul][3]);
            ldsm4t(src1 + uo, wb[ul][4], wb[ul][5], wb[ul][6], wb[ul][7]);
        }
        while (clock() - tpub < ((P.dly >> 10) & 31) * 64) {}
        mb_first<2, 512>(psrc, pn, pv);
        if (tid == 0) TRACE(18);
        const int nA = (hA + 1) * 64 - u0;
        combine_unit(SB, psrc, pn, pv, warp, warp < nA, lane);
        bar_sync(3, 288);
        if (tid == 0) TRACE(6);
        float acc[2][4][4] = {};
#pragma unroll
        for (int ul = 0; ul < 9; ul++) {
            const uint4 a = lds128((ul < nA) == (g < 4) ? SB + OFF_AFR + ul * 64 + t * 16 : SB + OFF_PVC + 48);
#pragma unroll
            for (int i = 0; i < 4; i++) mma16816(acc[ul & 1][i], a.x, a.y, a.z, a.w, wb[ul][2 * i], wb[ul][2 * i + 1]);
        }
        float v0, v1;
        {
            const int i = g & 3;
            float e[4][2];
#pragma unroll
            for (int k = 0; k < 4; k++) {
                e[k][0] = (acc[0][k][0] + acc[0][k][2]) + (acc[1][k][0] + acc[1][k][2]);
                e[k][1] = (acc[0][k][1] + acc[0][k][3]) + (acc[1][k][1] + acc[1][k][3]);
            }
            v0 = (i & 2) ? ((i & 1) ? e[3][0] : e[2][0]) : ((i & 1) ? e[1][0] : e[0][0]);
            v1 = (i & 2) ? ((i & 1) ? e[3][1] : e[2][1]) : ((i & 1) ? e[1][1] : e[0][1]);
        }
        if (a4) mb_put2f(mb + o4, v0, v1);
    }
    if (tid == 0) TRACE(7);
    if (!full) return;
    asm volatile("bar.arrive 10, 320;" ::: "memory");

    {
        mbar_wait(BAR(g_wo), 0);
        mbar_wait(BAR(g_wo + 1), 0);
        uint32_t b[8][4];
        const uint32_t src = SB + OFF_CKV + lane * 128 + ((warp ^ (lane & 7)) << 4);
#pragma unroll
        for (int s2 = 0; s2 < 8; s2++) ldsm4t(src + s2 * 4096, b[s2][0], b[s2][1], b[s2][2], b[s2][3]);
        bar_sync(8, 320);
        if (tid == 0) TRACE(8);
        float c[4][4] = {};
#pragma unroll
        for (int s2 = 0; s2 < 8; s2++) {
            const uint4 a = lds128(SB + OFF_CTX + s2 * 64 + t * 16);
            mma16816(c[(s2 & 1) * 2], a.x, 0, a.y, 0, b[s2][0], b[s2][1]);
            mma16816(c[(s2 & 1) * 2 + 1], a.z, 0, a.w, 0, b[s2][2], b[s2][3]);
        }
        if (lane < 4) mb_put2f(mb + o5, (c[0][0] + c[1][0]) + (c[2][0] + c[3][0]), (c[0][1] + c[1][1]) + (c[2][1] + c[3][1]));
    }
    asm volatile("bar.arrive 11, 288;" ::: "memory");
    if (tid == 0) TRACE(9);

    {
        mbar_wait(BAR(g_gu), 0);
        mbar_wait(BAR(g_gu + 1), 0);
        uint32_t b[7][4];
        const uint32_t src = SB + OFF_CKV + 4 * UNIT + lane * 128 + ((warp ^ (lane & 7)) << 4);
#pragma unroll
        for (int s2 = 0; s2 < 7; s2++) ldsm4t(src + s2 * 4096, b[s2][0], b[s2][1], b[s2][2], b[s2][3]);
        const uint32_t gdst = mapa(SB + OFF_GU + r * 512 + (warp * 4 + t) * 16, g & 3), gbar = mapa(BAR(B_GU), g & 3);
        mbar_wait_cl(BAR(B_H), 0);
        if (tid == 0) TRACE(10);
        float c[4][4] = {};
        const uint32_t one = 0x3f803f80u;
#pragma unroll
        for (int s2 = 0; s2 < 7; s2++) {
            const uint4 a = lds128(SB + OFF_H + (r >> 1) * 448 + s2 * 64 + t * 16);
            mma16816(c[(s2 & 1) * 2], a.x, one, a.y, one, b[s2][0], b[s2][1]);
            mma16816(c[(s2 & 1) * 2 + 1], a.z, one, a.w, one, b[s2][2], b[s2][3]);
        }
        if (g < 4)
            st_async_v4(gdst, __float_as_uint((c[0][0] + c[1][0]) + (c[2][0] + c[3][0])),
                        __float_as_uint((c[0][1] + c[1][1]) + (c[2][1] + c[3][1])), __float_as_uint((c[0][2] + c[1][2]) + (c[2][2] + c[3][2])),
                        __float_as_uint((c[0][3] + c[1][3]) + (c[2][3] + c[3][3])), gbar);
    }
    {
        mbar_wait(BAR(g_wd), 0);
        uint32_t b[4][4];
        const uint32_t src = SB + OFF_CKV + 8 * UNIT + lane * 128 + ((warp ^ (lane & 7)) << 4);
        ldsm4t(src, b[0][0], b[0][1], b[0][2], b[0][3]);
        ldsm4t(src + 4096, b[1][0], b[1][1], b[1][2], b[1][3]);
        ldsm4t(src + UNIT, b[2][0], b[2][1], b[2][2], b[2][3]);
        ldsm4t(src + UNIT + 4096, b[3][0], b[3][1], b[3][2], b[3][3]);
        mbar_wait_cl(BAR(B_GU), 0);
        if (tid == 0) TRACE(11);
        const uint32_t ga = SB + OFF_GU + (((g & 3) * 2 + (g >> 2)) * 4 + t) * 16;
        const uint4 p0 = lds128(ga), p1 = lds128(ga + 512), p2 = lds128(ga + 1024), p3 = lds128(ga + 1536);
        const float mean = __uint_as_float(lds32(SB + OFF_MISC + 8)), inv = __uint_as_float(lds32(SB + OFF_MISC + 12));
        const float g0 = bf16r(((__uint_as_float(p0.x) + __uint_as_float(p2.x)) - mean * (__uint_as_float(p0.z) + __uint_as_float(p2.z))) * inv);
        const float g1 = bf16r(((__uint_as_float(p0.y) + __uint_as_float(p2.y)) - mean * (__uint_as_float(p0.w) + __uint_as_float(p2.w))) * inv);
        const float u0v = bf16r(((__uint_as_float(p1.x) + __uint_as_float(p3.x)) - mean * (__uint_as_float(p1.z) + __uint_as_float(p3.z))) * inv);
        const float u1v = bf16r(((__uint_as_float(p1.y) + __uint_as_float(p3.y)) - mean * (__uint_as_float(p1.w) + __uint_as_float(p3.w))) * inv);
        const float s0 = bf16r(__fdividef(1.f, 1.f + __expf(-g0))), s1 = bf16r(__fdividef(1.f, 1.f + __expf(-g1)));
        const uint32_t hw = pack2(s0 * u0v, s1 * u1v);
        uint32_t a[8];
#pragma unroll
        for (int k = 0; k < 8; k++) a[k] = __shfl_sync(~0u, hw, k * 4 + t);
        float c0[4] = {}, c1[4] = {}, c2[4] = {}, c3[4] = {};
        mma16816(c0, a[0], 0, a[4], 0, b[0][0], b[0][1]);
        mma16816(c1, a[0], 0, a[4], 0, b[2][0], b[2][1]);
        mma16816(c2, a[1], 0, a[5], 0, b[0][2], b[0][3]);
        mma16816(c3, a[1], 0, a[5], 0, b[2][2], b[2][3]);
        mma16816(c0, a[2], 0, a[6], 0, b[1][0], b[1][1]);
        mma16816(c1, a[2], 0, a[6], 0, b[3][0], b[3][1]);
        mma16816(c2, a[3], 0, a[7], 0, b[1][2], b[1][3]);
        mma16816(c3, a[3], 0, a[7], 0, b[3][2], b[3][3]);
        if (a6) mb_put2f(mb + o6, (g & 1) ? c1[0] + c3[0] : c0[0] + c2[0], (g & 1) ? c1[1] + c3[1] : c0[1] + c2[1]);
    }
    asm volatile("bar.arrive 12, 288;" ::: "memory");
    if (tid == 0) TRACE(12);
}

__device__ float f_q[4096], f_qa[16 * 1024], f_s[16 * 8192], f_cc[64 * 16 * 1024], f_ctx[4096], f_h[448], f_hh[1792];

__device__ __forceinline__ void block_ln(const float* v  , float* o  ) {
    float a[14];
    const int lane = threadIdx.x & 31;
#pragma unroll
    for (int i = 0; i < 14; i++) a[i] = v[lane + 32 * i];
    float mb, den;
    ln_stats(a, mb, den);
    for (int i = threadIdx.x; i < 448; i += blockDim.x) o[i] = bf16r(ln_apply(v[i], mb, den));
    __syncthreads();
}
__global__ void fb_q(const __nv_bfloat16* x, const __nv_bfloat16* wq) {
    __shared__ float xs[448], xn[448];
    for (int i = threadIdx.x; i < 448; i += blockDim.x) xs[i] = __bfloat162float(x[i]);
    __syncthreads();
    block_ln(xs, xn);
    const int c = blockIdx.x * blockDim.x + threadIdx.x;
    float a = 0.f;
    for (int m = 0; m < 448; m++) a += xn[m] * __bfloat162float(wq[(size_t)m * 4096 + c]);
    f_q[c] = bf16r(a);
}
__global__ void fb_qabs(const __nv_bfloat16* wuk) {
    const int row = blockIdx.x * 8 + (threadIdx.x >> 5), lane = threadIdx.x & 31;
    const int h = row & 15, c = row >> 4;
    float a = 0.f;
    for (int d = lane; d < 256; d += 32) a += f_q[h * 256 + d] * __bfloat162float(wuk[(size_t)row * 256 + d]);
    for (int o = 16; o; o >>= 1) a += __shfl_xor_sync(~0u, a, o);
    if (lane == 0) f_qa[h * 1024 + c] = a * 0.0625f;
}
__global__ void fb_scores(const __nv_bfloat16* ckv) {
    const int k = blockIdx.x * 8 + (threadIdx.x >> 5), lane = threadIdx.x & 31;
    float a[16] = {};
    for (int c = lane; c < 1024; c += 32) {
        const float v = __bfloat162float(ckv[(size_t)k * 1024 + c]);
#pragma unroll
        for (int h = 0; h < 16; h++) a[h] += v * f_qa[h * 1024 + c];
    }
#pragma unroll
    for (int h = 0; h < 16; h++) {
        for (int o = 16; o; o >>= 1) a[h] += __shfl_xor_sync(~0u, a[h], o);
        if (lane == 0) f_s[h * 8192 + k] = a[h];
    }
}
__global__ void fb_softmax() {
    __shared__ float red[32];
    float* s = f_s + blockIdx.x * 8192;
    float m = -INFINITY;
    for (int i = threadIdx.x; i < 8192; i += blockDim.x) m = fmaxf(m, s[i]);
    for (int o = 16; o; o >>= 1) m = fmaxf(m, __shfl_xor_sync(~0u, m, o));
    if ((threadIdx.x & 31) == 0) red[threadIdx.x >> 5] = m;
    __syncthreads();
    m = red[0];
    for (int i = 1; i < (int)(blockDim.x >> 5); i++) m = fmaxf(m, red[i]);
    __syncthreads();
    float l = 0.f;
    for (int i = threadIdx.x; i < 8192; i += blockDim.x) { const float e = __expf(s[i] - m); s[i] = e; l += e; }
    for (int o = 16; o; o >>= 1) l += __shfl_xor_sync(~0u, l, o);
    if ((threadIdx.x & 31) == 0) red[threadIdx.x >> 5] = l;
    __syncthreads();
    l = 0.f;
    for (int i = 0; i < (int)(blockDim.x >> 5); i++) l += red[i];
    const float inv = 1.f / l;
    for (int i = threadIdx.x; i < 8192; i += blockDim.x) s[i] *= inv;
}
__global__ void fb_pv(const __nv_bfloat16* ckv) {
    const int c = blockIdx.y * 256 + threadIdx.x, kb = blockIdx.x * 128;
    float a[16] = {};
    for (int k = kb; k < kb + 128; k++) {
        const float v = __bfloat162float(ckv[(size_t)k * 1024 + c]);
#pragma unroll
        for (int h = 0; h < 16; h++) a[h] += v * f_s[h * 8192 + k];
    }
#pragma unroll
    for (int h = 0; h < 16; h++) f_cc[(blockIdx.x * 16 + h) * 1024 + c] = a[h];
}
__global__ void fb_ctx(const __nv_bfloat16* wuv) {
    __shared__ float cc[1024];
    const int h = blockIdx.x;
    for (int c = threadIdx.x; c < 1024; c += 256) {
        float a = 0.f;
        for (int i = 0; i < 64; i++) a += f_cc[(i * 16 + h) * 1024 + c];
        cc[c] = a;
    }
    __syncthreads();
    float a = 0.f;
    for (int c = 0; c < 1024; c++) a += cc[c] * __bfloat162float(wuv[(size_t)c * 4096 + h * 256 + threadIdx.x]);
    f_ctx[h * 256 + threadIdx.x] = bf16r(a);
}
__global__ void fb_o(const __nv_bfloat16* x, const __nv_bfloat16* wo) {
    __shared__ float red[8][32];
    const int m = blockIdx.x * 32 + (threadIdx.x & 31), p = threadIdx.x >> 5;
    float a = 0.f;
    for (int i = p * 512; i < p * 512 + 512; i++) a += f_ctx[i] * __bfloat162float(wo[(size_t)i * 448 + m]);
    red[p][threadIdx.x & 31] = a;
    __syncthreads();
    if (p == 0) {
        for (int i = 1; i < 8; i++) a += red[i][threadIdx.x];
        f_h[m] = bf16r(__bfloat162float(x[m]) + bf16r(a));
    }
}
__global__ void fb_gu(const __nv_bfloat16* wg, const __nv_bfloat16* wu) {
    __shared__ float hs[448], hn[448];
    for (int i = threadIdx.x; i < 448; i += blockDim.x) hs[i] = f_h[i];
    __syncthreads();
    block_ln(hs, hn);
    const int f = blockIdx.x * 64 + threadIdx.x;
    float a = 0.f, b = 0.f;
    for (int m = 0; m < 448; m++) {
        a += hn[m] * __bfloat162float(wg[(size_t)m * 1792 + f]);
        b += hn[m] * __bfloat162float(wu[(size_t)m * 1792 + f]);
    }
    f_hh[f] = bf16r(bf16r(1.f / (1.f + __expf(-bf16r(a)))) * bf16r(b));
}
__global__ void fb_down(const __nv_bfloat16* wd, __nv_bfloat16* out) {
    __shared__ float red[8][32];
    const int m = blockIdx.x * 32 + (threadIdx.x & 31), p = threadIdx.x >> 5;
    float a = 0.f;
    for (int i = p * 224; i < p * 224 + 224; i++) a += f_hh[i] * __bfloat162float(wd[(size_t)i * 448 + m]);
    red[p][threadIdx.x & 31] = a;
    __syncthreads();
    if (p == 0) {
        for (int i = 1; i < 8; i++) a += red[i][threadIdx.x];
        out[m] = __float2bfloat16_rn(f_h[m] + bf16r(a));
    }
}

typedef CUresult (*EncodeFn)(CUtensorMap*, CUtensorMapDataType, cuuint32_t, void*, const cuuint64_t*, const cuuint64_t*,
                             const cuuint32_t*, const cuuint32_t*, CUtensorMapInterleave, CUtensorMapSwizzle,
                             CUtensorMapL2promotion, CUtensorMapFloatOOBfill);

bool encode3(EncodeFn enc, CUtensorMap* m, const void* p, uint64_t rows, uint64_t rowbytes) {
    cuuint64_t dim[3] = {64, rows, rowbytes / 128};
    cuuint64_t str[2] = {rowbytes, 128};
    cuuint32_t box[3] = {64, 16, 4}, es[3] = {1, 1, 1};
    return enc(m, CU_TENSOR_MAP_DATA_TYPE_BFLOAT16, 3, const_cast<void*>(p), dim, str, box, es, CU_TENSOR_MAP_INTERLEAVE_NONE,
               CU_TENSOR_MAP_SWIZZLE_128B, CU_TENSOR_MAP_L2_PROMOTION_NONE, CU_TENSOR_MAP_FLOAT_OOB_FILL_NONE) == CUDA_SUCCESS;
}
bool encode2(EncodeFn enc, CUtensorMap* m, const void* p, uint64_t rows, uint64_t cols, uint32_t boxrows) {
    cuuint64_t dim[2] = {cols, rows};
    cuuint64_t str[1] = {cols * 2};
    cuuint32_t box[2] = {64, boxrows}, es[2] = {1, 1};
    return enc(m, CU_TENSOR_MAP_DATA_TYPE_BFLOAT16, 2, const_cast<void*>(p), dim, str, box, es, CU_TENSOR_MAP_INTERLEAVE_NONE,
               CU_TENSOR_MAP_SWIZZLE_128B, CU_TENSOR_MAP_L2_PROMOTION_NONE, CU_TENSOR_MAP_FLOAT_OOB_FILL_NONE) == CUDA_SUCCESS;
}

int g_force_fallback = 0;
int g_force_nc = 0;
int g_window = 0x2233;
unsigned g_dly = (24u << 10) | (8u << 15);

}

extern "C" void kernel_launch(void* const* d_in, const int* in_sizes, int n_in, void* d_out, int out_size) {
    const __nv_bfloat16* x = (const __nv_bfloat16*)d_in[0];
    const __nv_bfloat16* ckv = (const __nv_bfloat16*)d_in[1];
    const __nv_bfloat16* wq = (const __nv_bfloat16*)d_in[2];
    const __nv_bfloat16* wuk = (const __nv_bfloat16*)d_in[3];
    const __nv_bfloat16* wuv = (const __nv_bfloat16*)d_in[4];
    const __nv_bfloat16* wo = (const __nv_bfloat16*)d_in[5];
    const __nv_bfloat16* wg = (const __nv_bfloat16*)d_in[7];
    const __nv_bfloat16* wu = (const __nv_bfloat16*)d_in[8];
    const __nv_bfloat16* wd = (const __nv_bfloat16*)d_in[9];
    __nv_bfloat16* out = (__nv_bfloat16*)d_out;
    cudaStream_t st = cudaStreamPerThread;

    static int s_init = 0, s_nc = 0;
    static EncodeFn s_enc = nullptr;
    cudaLaunchConfig_t cfg = {};
    cudaLaunchAttribute at[1];
    at[0].id = cudaLaunchAttributeClusterDimension;
    at[0].val.clusterDim.x = 4; at[0].val.clusterDim.y = 1; at[0].val.clusterDim.z = 1;
    cfg.blockDim = dim3(NTHR); cfg.dynamicSmemBytes = SMEM_BYTES + 128; cfg.stream = st; cfg.attrs = at; cfg.numAttrs = 1;
    if (!s_init) {
        s_init = 1;
        void* fn = nullptr;
        cudaDriverEntryPointQueryResult qr;
        if (cudaGetDriverEntryPoint("cuTensorMapEncodeTiled", &fn, cudaEnableDefault, &qr) == cudaSuccess &&
            qr == cudaDriverEntryPointSuccess)
            s_enc = (EncodeFn)fn;
        int nc = 0;
        cfg.gridDim = dim3(4 * NC_MAX);
        if (cudaFuncSetAttribute(fused_kernel, cudaFuncAttributeMaxDynamicSharedMemorySize, SMEM_BYTES + 128) == cudaSuccess &&
            cudaOccupancyMaxActiveClusters(&nc, fused_kernel, &cfg) == cudaSuccess)
            s_nc = nc > NC_MAX ? NC_MAX : nc;
        (void)cudaGetLastError();
    }
    if (g_force_nc && g_force_nc < s_nc) s_nc = g_force_nc;
    Params P;
    bool ok = s_enc != nullptr && s_nc >= NC_MIN && !g_force_fallback;
    ok = ok && encode3(s_enc, &P.wq, wq, 448, 8192) && encode3(s_enc, &P.wuk, wuk, 1024, 8192) &&
         encode3(s_enc, &P.ckv, ckv, 8192, 2048) && encode3(s_enc, &P.wuv, wuv, 1024, 8192) &&
         encode2(s_enc, &P.wo, wo, 4096, 448, 64) && encode2(s_enc, &P.wg, wg, 448, 1792, 112) &&
         encode2(s_enc, &P.wu, wu, 448, 1792, 112) && encode2(s_enc, &P.wd, wd, 1792, 448, 64);
    if (ok) {
        P.x = x; P.out = out; P.NC = s_nc; P.W = g_window; P.dly = g_dly;
        const int N = 4 * s_nc;
        int ustart[4 * NC_MAX + 1], kstart[NC_MAX + 1];
        {
            const int kbase = 512 / s_nc, kext = 512 - kbase * s_nc;
            kstart[0] = 0;
            for (int jj = 0; jj < s_nc; jj++) kstart[jj + 1] = kstart[jj] + kbase + (jj >= s_nc - kext ? 1 : 0);
            int cap = 0;
            for (int c = 0; c < N; c++) cap += (kstart[(c >> 2) + 1] - kstart[c >> 2] > 17) ? 8 : 9;
            const bool deep = cap >= 1024;
            P.RS = deep ? 5 : 3;
            int nine = 0;
            for (int c = 0; c < N; c++) nine += (!deep || kstart[(c >> 2) + 1] - kstart[c >> 2] <= 17) ? 1 : 0;
            const int uext = 1024 - 8 * N;
            ustart[0] = 0;
            for (int c = 0, i = 0; c < N; c++) {
                int extra = 0;
                if (!deep || kstart[(c >> 2) + 1] - kstart[c >> 2] <= 17) { extra = (i + 1) * uext / nine - i * uext / nine; i++; }
                ustart[c + 1] = ustart[c] + 8 + extra;
            }
        }
        auto owner = [&](int u) { int c = 0; while (ustart[c + 1] <= u) c++; return c; };
        for (int c = 0; c < 4 * NC_MAX; c++) {
            if (c >= N) { P.tab[c] = make_uint2(0, 0); continue; }
            const int jj = c >> 2, u0 = ustart[c], nu = ustart[c + 1] - u0;
            const int k0 = kstart[jj], nk = kstart[jj + 1] - k0;
            const int h7 = (c / 7) & 15, mb7 = c % 7, hA = u0 >> 6, hB = (u0 + nu - 1) >> 6;
            const int ns = owner(h7 * 64 + 63) - owner(h7 * 64) + 1;
            P.tab[c].x = u0 | (nu << 10) | (k0 << 14) | (nk << 23);
            P.tab[c].y = h7 | (mb7 << 4) | ((c - owner(hA * 64)) << 8) | ((c - owner(hB * 64)) << 12) | (ns << 16);
        }
        cfg.gridDim = dim3(4 * s_nc);
        cudaLaunchKernelEx(&cfg, fused_kernel, P);
        return;
    }
    fb_q<<<16, 256, 0, st>>>(x, wq);
    fb_qabs<<<2048, 256, 0, st>>>(wuk);
    fb_scores<<<1024, 256, 0, st>>>(ckv);
    fb_softmax<<<16, 1024, 0, st>>>();
    fb_pv<<<dim3(64, 4), 256, 0, st>>>(ckv);
    fb_ctx<<<16, 256, 0, st>>>(wuv);
    fb_o<<<14, 256, 0, st>>>(x, wo);
    fb_gu<<<28, 64, 0, st>>>(wg, wu);
    fb_down<<<14, 256, 0, st>>>(wd, out);
}
```

```cpp
#include <cuda_runtime.h>
#include <cuda_bf16.h>
#include <cuda.h>
#include <stdint.h>
#include <limits.h>

namespace {

constexpr int NC_MAX = 32, NC_MIN = 29;
constexpr int NTHR = 512;

constexpr uint32_t UNIT = 8192;
constexpr uint32_t OFF_CKV = 0;
constexpr uint32_t OFF_WA = 18 * UNIT;
constexpr uint32_t OFF_X = OFF_WA + 9 * UNIT;
constexpr uint32_t OFF_SLOT = OFF_X;
constexpr uint32_t OFF_PBUF = OFF_X + 3 * 2048;
constexpr uint32_t PSTRIDE = 1088;
constexpr uint32_t OFF_BAR = OFF_PBUF + 4 * PSTRIDE;
constexpr uint32_t OFF_MISC = OFF_BAR + 42 * 8;
constexpr uint32_t OFF_WGT = OFF_CKV + 10 * UNIT;
constexpr uint32_t OFF_REF = OFF_MISC + 16;
constexpr uint32_t OFF_PVC = OFF_REF + 48;
constexpr uint32_t SMEM_BYTES = OFF_PVC + 64;
constexpr uint32_t OFF_QST = OFF_PBUF;
constexpr uint32_t OFF_TILE = OFF_X;
constexpr uint32_t OFF_CTX = OFF_X + 9216;
constexpr uint32_t OFF_AFR = OFF_X + 9728;
constexpr uint32_t OFF_H = OFF_X;
constexpr uint32_t OFF_GU = OFF_X + 1024;
static_assert(OFF_AFR + 576 <= OFF_BAR, "staging overflow");
static_assert(SMEM_BYTES + 128 <= 232448, "smem overflow");

enum { B_S0 = 26, B_P0 = 31, B_H = 37, B_GU = 38, G_P1 = 39, G_QA = 40, NBARS = 41 };

struct __align__(64) Params {
    CUtensorMap wq, wuk, ckv, wuv, wo, wg, wu, wd;
    const __nv_bfloat16* x;
    __nv_bfloat16* out;
    int NC;
    int W;
    unsigned dly;
    int RS;
    uint2 tab[4 * NC_MAX];
};

constexpr uint32_t MB1 = 0;
constexpr uint32_t MB2 = MB1 + 112 * 1024;
constexpr uint32_t MB3 = MB2 + 32768;
constexpr uint32_t MBM = MB3 + 1024 * 1024;
constexpr uint32_t MB4 = MBM + 16384;
constexpr uint32_t MB5 = MB4 + 16 * 12 * 1024;
constexpr uint32_t MB6 = MB5 + 16 * 1792;
constexpr uint32_t MB_SET = (MB6 + 4 * 28 * 28 * 32 + 1023) / 1024 * 1024;
__device__ __align__(1024) unsigned char g_mb[2 * MB_SET];
__device__ unsigned g_epoch;
#define TRACE(i) do {} while (0)

constexpr int SPIN_LIMIT = 1 << 18;
__device__ __forceinline__ void mbar_init(uint32_t b, uint32_t c) {
    asm volatile("mbarrier.init.shared::cta.b64 [%0], %1;" ::"r"(b), "r"(c) : "memory");
}
__device__ __forceinline__ void mbar_expect(uint32_t b, uint32_t bytes) {
    asm volatile("mbarrier.arrive.expect_tx.shared::cta.b64 _, [%0], %1;" ::"r"(b), "r"(bytes) : "memory");
}
__device__ __forceinline__ void mbar_arrive(uint32_t b) {
    asm volatile("mbarrier.arrive.shared::cta.b64 _, [%0];" ::"r"(b) : "memory");
}
__device__ __forceinline__ bool mbar_try(uint32_t b, uint32_t ph) {
    uint32_t ok;
    asm volatile("{.reg .pred p; mbarrier.try_wait.parity.shared::cta.b64 p, [%1], %2; selp.u32 %0,1,0,p;}"
                 : "=r"(ok) : "r"(b), "r"(ph) : "memory");
    return ok;
}
__device__ __forceinline__ bool mbar_test(uint32_t b, uint32_t ph) {
    uint32_t ok;
    asm volatile("{.reg .pred p; mbarrier.test_wait.parity.shared::cta.b64 p, [%1], %2; selp.u32 %0,1,0,p;}"
                 : "=r"(ok) : "r"(b), "r"(ph) : "memory");
    return ok;
}
__device__ __forceinline__ void mbar_wait(uint32_t b, uint32_t ph) {
#pragma unroll 1
    for (int i = 0; i < SPIN_LIMIT; i++)
        if (mbar_try(b, ph)) return;
}
__device__ __forceinline__ void mbar_wait_cl(uint32_t b, uint32_t ph) {
#pragma unroll 1
    for (int i = 0; i < SPIN_LIMIT; i++) {
        uint32_t ok;
        asm volatile("{.reg .pred p; mbarrier.try_wait.parity.acquire.cluster.shared::cta.b64 p, [%1], %2; selp.u32 %0,1,0,p;}"
                     : "=r"(ok) : "r"(b), "r"(ph) : "memory");
        if (ok) return;
    }
}
__device__ __forceinline__ void tma2p(uint32_t dst, const CUtensorMap* m, int x, int y, uint32_t bar, unsigned long long pol) {
    asm volatile("cp.async.bulk.tensor.2d.shared::cluster.global.mbarrier::complete_tx::bytes.L2::cache_hint [%0], [%1, {%3, %4}], [%2], %5;"
                 ::"r"(dst), "l"(m), "r"(bar), "r"(x), "r"(y), "l"(pol) : "memory");
}
__device__ __forceinline__ void tma3p(uint32_t dst, const CUtensorMap* m, int x, int y, int z, uint32_t bar, unsigned long long pol) {
    asm volatile("cp.async.bulk.tensor.3d.shared::cluster.global.mbarrier::complete_tx::bytes.L2::cache_hint [%0], [%1, {%3, %4, %5}], [%2], %6;"
                 ::"r"(dst), "l"(m), "r"(bar), "r"(x), "r"(y), "r"(z), "l"(pol) : "memory");
}
__device__ __forceinline__ uint32_t mapa(uint32_t a, uint32_t rank) {
    uint32_t r;
    asm("mapa.shared::cluster.u32 %0, %1, %2;" : "=r"(r) : "r"(a), "r"(rank));
    return r;
}
__device__ __forceinline__ void st_async_v4(uint32_t a, uint32_t x, uint32_t y, uint32_t z, uint32_t w, uint32_t bar) {
    asm volatile("st.async.weak.shared::cluster.mbarrier::complete_tx::bytes.v4.b32 [%0], {%1,%2,%3,%4}, [%5];"
                 ::"r"(a), "r"(x), "r"(y), "r"(z), "r"(w), "r"(bar) : "memory");
}
__device__ __forceinline__ void st_async_b32(uint32_t a, uint32_t x, uint32_t bar) {
    asm volatile("st.async.weak.shared::cluster.mbarrier::complete_tx::bytes.b32 [%0], %1, [%2];"
                 ::"r"(a), "r"(x), "r"(bar) : "memory");
}
__device__ __forceinline__ void ldsm4(uint32_t a, uint32_t& r0, uint32_t& r1, uint32_t& r2, uint32_t& r3) {
    asm volatile("ldmatrix.sync.aligned.m8n8.x4.shared.b16 {%0,%1,%2,%3}, [%4];"
                 : "=r"(r0), "=r"(r1), "=r"(r2), "=r"(r3) : "r"(a) : "memory");
}
__device__ __forceinline__ void ldsm4t(uint32_t a, uint32_t& r0, uint32_t& r1, uint32_t& r2, uint32_t& r3) {
    asm volatile("ldmatrix.sync.aligned.m8n8.x4.trans.shared.b16 {%0,%1,%2,%3}, [%4];"
                 : "=r"(r0), "=r"(r1), "=r"(r2), "=r"(r3) : "r"(a) : "memory");
}
__device__ __forceinline__ void mma16816(float (&c)[4], uint32_t a0, uint32_t a1, uint32_t a2, uint32_t a3, uint32_t b0, uint32_t b1) {
    asm("mma.sync.aligned.m16n8k16.row.col.f32.bf16.bf16.f32 {%0,%1,%2,%3}, {%4,%5,%6,%7}, {%8,%9}, {%0,%1,%2,%3};"
                 : "+f"(c[0]), "+f"(c[1]), "+f"(c[2]), "+f"(c[3]) : "r"(a0), "r"(a1), "r"(a2), "r"(a3), "r"(b0), "r"(b1));
}
__device__ __forceinline__ uint4 lds128(uint32_t a) {
    uint4 v;
    asm volatile("ld.shared.v4.u32 {%0,%1,%2,%3}, [%4];" : "=r"(v.x), "=r"(v.y), "=r"(v.z), "=r"(v.w) : "r"(a) : "memory");
    return v;
}
__device__ __forceinline__ uint32_t lds32(uint32_t a) {
    uint32_t v;
    asm volatile("ld.shared.u32 %0, [%1];" : "=r"(v) : "r"(a) : "memory");
    return v;
}
__device__ __forceinline__ uint32_t lds32_acq(uint32_t a) {
    uint32_t v;
    asm volatile("ld.acquire.cta.shared.u32 %0, [%1];" : "=r"(v) : "r"(a) : "memory");
    return v;
}
__device__ __forceinline__ uint4 lds128_vol(uint32_t a) {
    uint4 v;
    asm volatile("ld.volatile.shared.v4.u32 {%0,%1,%2,%3}, [%4];" : "=r"(v.x), "=r"(v.y), "=r"(v.z), "=r"(v.w) : "r"(a) : "memory");
    return v;
}
__device__ __forceinline__ void sts128_vol(uint32_t a, uint4 v) {
    asm volatile("st.volatile.shared.v4.u32 [%0], {%1,%2,%3,%4};" ::"r"(a), "r"(v.x), "r"(v.y), "r"(v.z), "r"(v.w) : "memory");
}
__device__ __forceinline__ void red_add_rel(uint32_t a, uint32_t v) {
    asm volatile("red.release.cta.shared.add.u32 [%0], %1;" ::"r"(a), "r"(v) : "memory");
}
__device__ __forceinline__ void pv_wait(uint32_t pvc, int k) {
#pragma unroll 1
    for (int it = 0; it < SPIN_LIMIT * 8; it++)
        if ((int)lds32_acq(pvc + k * 4) >= 8) return;
}
__device__ __forceinline__ void sts128(uint32_t a, uint4 v) {
    asm volatile("st.shared.v4.u32 [%0], {%1,%2,%3,%4};" ::"r"(a), "r"(v.x), "r"(v.y), "r"(v.z), "r"(v.w) : "memory");
}
__device__ __forceinline__ void sts32(uint32_t a, uint32_t v) {
    asm volatile("st.shared.u32 [%0], %1;" ::"r"(a), "r"(v) : "memory");
}
__device__ __forceinline__ void sts16(uint32_t a, uint16_t v) {
    asm volatile("st.shared.u16 [%0], %1;" ::"r"(a), "h"(v) : "memory");
}
__device__ __forceinline__ void bar_sync(int id, int n) {
    asm volatile("bar.sync %0, %1;" ::"r"(id), "r"(n) : "memory");
}
__device__ __forceinline__ float bf16r(float v) { return __bfloat162float(__float2bfloat16_rn(v)); }
__device__ __forceinline__ uint32_t pack2(float lo, float hi) {
    __nv_bfloat162 t = __floats2bfloat162_rn(lo, hi);
    return *reinterpret_cast<uint32_t*>(&t);
}
__device__ __forceinline__ float bflo(uint32_t w) { return __uint_as_float(w << 16); }
__device__ __forceinline__ float bfhi(uint32_t w) { return __uint_as_float(w & 0xffff0000u); }
__device__ __forceinline__ float ex2(float x) {
    float y;
    asm("ex2.approx.ftz.f32 %0, %1;" : "=f"(y) : "f"(x));
    return y;
}
__device__ __forceinline__ uint32_t ldg_early(const uint32_t* p) {
    uint32_t v;
    asm volatile("ld.global.nc.u32 %0, [%1];" : "=r"(v) : "l"(p));
    return v;
}

__device__ __forceinline__ void mb_st2(unsigned char* p, uint32_t a, uint32_t b) {
    asm volatile("{.reg .b64 t; mov.b64 t, {%1,%2}; st.relaxed.gpu.global.b64 [%0], t;}" ::"l"(p), "r"(a), "r"(b) : "memory");
}
__device__ __forceinline__ void mb_put2(unsigned char* p, uint32_t a, uint32_t b) { mb_st2(p, a == 0u ? 0x80000000u : a, b); }
__device__ __forceinline__ void mb_put2f(unsigned char* p, float a, float b) { mb_put2(p, __float_as_uint(a), __float_as_uint(b)); }
__device__ __forceinline__ void mb_clear2(uint32_t off) {
    mb_st2(g_mb + off, 0u, 0u);
    mb_st2(g_mb + MB_SET + off, 0u, 0u);
}
__device__ __forceinline__ uint4 mb_ld4(const unsigned char* p) {
    uint4 v;
    asm volatile("{.reg .b64 a, b; ld.relaxed.gpu.global.v2.b64 {a, b}, [%4]; mov.b64 {%0,%1}, a; mov.b64 {%2,%3}, b;}"
                 : "=r"(v.x), "=r"(v.y), "=r"(v.z), "=r"(v.w) : "l"(p) : "memory");
    return v;
}
template <int N, int STRIDE>
__device__ __forceinline__ void mb_poll(const unsigned char* p, int n, uint4 (&v)[N]) {
#pragma unroll
    for (int i = 0; i < N; i++) v[i] = i < n ? mb_ld4(p + i * STRIDE) : make_uint4(0, 0, 0, 0);
#pragma unroll 1
    for (int it = 0; it < SPIN_LIMIT; it++) {
        uint32_t m = 0xffffffffu;
#pragma unroll
        for (int i = 0; i < N; i++)
            if (i < n) m = min(m, min(v[i].x, v[i].z));
        if (m != 0u) break;
#pragma unroll
        for (int i = 0; i < N; i++)
            if (i < n && (N > 4 || min(v[i].x, v[i].z) == 0u)) v[i] = mb_ld4(p + i * STRIDE);
    }
}
__device__ __forceinline__ void delay(uint32_t clks) {
    const uint32_t t0 = clock();
    while (clock() - t0 < clks) {}
}

template <int N, int STRIDE>
__device__ __forceinline__ void mb_first(const unsigned char* p, int n, uint4 (&v)[N]) {
#pragma unroll
    for (int i = 0; i < N; i++) v[i] = i < n ? mb_ld4(p + i * STRIDE) : make_uint4(0, 0, 0, 0);
}
__device__ __forceinline__ void ln_stats(const float (&v)[14], float& mb, float& den) {
    float s = 0.f;
#pragma unroll
    for (int i = 0; i < 14; i++) s += v[i];
#pragma unroll
    for (int o = 16; o; o >>= 1) s += __shfl_xor_sync(~0u, s, o);
    const float mean = s * (1.f / 448.f);
    float q = 0.f;
#pragma unroll
    for (int i = 0; i < 14; i++) { const float d = v[i] - mean; q += d * d; }
#pragma unroll
    for (int o = 16; o; o >>= 1) q += __shfl_xor_sync(~0u, q, o);
    mb = bf16r(mean);
    den = bf16r(__fsqrt_rn(bf16r(bf16r(q * (1.f / 448.f)) + 1e-5f)));
}
__device__ __forceinline__ void ln_stats1(const float (&v)[14], float c, float& mb, float& den) {
    float s0 = 0.f, s1 = 0.f, q0 = 0.f, q1 = 0.f;
#pragma unroll
    for (int i = 0; i < 7; i++) {
        const float d0 = v[2 * i] - c, d1 = v[2 * i + 1] - c;
        s0 += d0; s1 += d1; q0 += d0 * d0; q1 += d1 * d1;
    }
    float s = s0 + s1, q = q0 + q1;
#pragma unroll
    for (int o = 16; o; o >>= 1) { s += __shfl_xor_sync(~0u, s, o); q += __shfl_xor_sync(~0u, q, o); }
    const float md = s * (1.f / 448.f);
    mb = bf16r(c + md);
    den = bf16r(__fsqrt_rn(bf16r(bf16r(fmaxf(q * (1.f / 448.f) - md * md, 0.f)) + 1e-5f)));
}
__device__ __forceinline__ float ln_apply(float v, float mb, float den) { return __fdiv_rn(bf16r(v - mb), den); }
__device__ __forceinline__ float ln_apply_r(float v, float mb, float rden) { return bf16r(v - mb) * rden; }

__device__ __forceinline__ uint32_t frag_off(int w) {
    const int s = w >> 3, half = (w >> 2) & 1, t = w & 3;
    return (uint32_t)((((s >> 1) * 4 + t) * 4 + (s & 1) * 2 + half) * 4);
}
__device__ __forceinline__ int f2o(float f) { const int i = __float_as_int(f); return i ^ ((i >> 31) & 0x7fffffff); }
__device__ __forceinline__ float o2f(int i) { return __int_as_float(i ^ ((i >> 31) & 0x7fffffff)); }

__device__ __forceinline__ void combine_unit(uint32_t SB, const unsigned char* src, int n, uint4 (&v)[2], int ul, bool isA, int lane) {
#pragma unroll 1
    for (int it = 0; it < SPIN_LIMIT; it++) {
        uint32_t m = 0xffffffffu;
        if (n > 0) m = min(m, min(v[0].x, v[0].z));
        if (n > 1) m = min(m, min(v[1].x, v[1].z));
        if (m != 0u) break;
        if (n > 0 && min(v[0].x, v[0].z) == 0u) v[0] = mb_ld4(src);
        if (n > 1 && min(v[1].x, v[1].z) == 0u) v[1] = mb_ld4(src + 512);
    }
    const uint32_t tile = SB + OFF_TILE + ul * 1024, wgt = SB + OFF_WGT + (isA ? 0 : 128);
    sts128(tile + lane * 16, v[0]);
    sts128(tile + 512 + lane * 16, v[1]);
    bar_sync(2, 352);
    const int t = lane & 3;
    uint32_t b[8];
    const uint32_t ts = tile + ((lane & 7) + (lane & 8)) * 32 + (lane >> 4) * 16;
    ldsm4t(ts, b[0], b[1], b[2], b[3]);
    ldsm4t(ts + 512, b[4], b[5], b[6], b[7]);
    const uint4 w0 = lds128(wgt + t * 16), w1 = lds128(wgt + 64 + t * 16);
    float c0[4] = {}, c1[4] = {}, c2[4] = {}, c3[4] = {};
    mma16816(c0, w0.x, w0.y, w0.z, w0.w, b[0], b[1]);
    mma16816(c1, w0.x, w0.y, w0.z, w0.w, b[2], b[3]);
    mma16816(c2, w1.x, w1.y, w1.z, w1.w, b[4], b[5]);
    mma16816(c3, w1.x, w1.y, w1.z, w1.w, b[6], b[7]);
    const float v0 = (c0[0] + c0[2]) + (c2[0] + c2[2]), v1 = (c0[1] + c0[3]) + (c2[1] + c2[3]);
    const float v2 = (c1[0] + c1[2]) + (c3[0] + c3[2]), v3 = (c1[1] + c1[3]) + (c3[1] + c3[3]);
    const uint32_t a0 = pack2(v0, v1), a2 = pack2(v2, v3);
    const uint32_t a1 = pack2(v0 - bflo(a0), v1 - bfhi(a0)), a3 = pack2(v2 - bflo(a2), v3 - bfhi(a2));
    if (lane < 4) sts128(SB + OFF_AFR + ul * 64 + t * 16, make_uint4(a0, a1, a2, a3));
}

__device__ __forceinline__ void qabs_unit(uint32_t SB, unsigned char* dst, int ul, bool second_head, uint32_t bar, int lane) {
    const int row = (lane & 7) + (lane & 8), cs = lane >> 4;
    const uint32_t qs = SB + OFF_QST + (second_head ? 512 : 0) + (lane & 3) * 16;
    uint4 q[8];
#pragma unroll
    for (int s2 = 0; s2 < 8; s2++) q[s2] = lds128(qs + s2 * 64);
    mbar_wait(bar, 0);
    float c[4][4] = {};
    const uint32_t a0 = SB + OFF_WA + ul * UNIT + row * 128;
#pragma unroll
    for (int s2 = 0; s2 < 8; s2++) {
        uint32_t r0, r1, r2, r3, r4, r5, r6, r7;
        ldsm4(a0 + (s2 >> 1) * 2048 + ((((s2 & 1) * 4 + cs) ^ (row & 7)) << 4), r0, r1, r2, r3);
        ldsm4(a0 + (s2 >> 1) * 2048 + ((((s2 & 1) * 4 + 2 + cs) ^ (row & 7)) << 4), r4, r5, r6, r7);
        mma16816(c[(s2 & 1) * 2], r0, r1, r2, r3, q[s2].x, q[s2].y);
        mma16816(c[(s2 & 1) * 2 + 1], r4, r5, r6, r7, q[s2].z, q[s2].w);
    }
    const float sc = 0.0625f * 1.4426950408889634f;
    const float lo = ((c[0][0] + c[1][0]) + (c[2][0] + c[3][0])) * sc, hi = ((c[0][2] + c[1][2]) + (c[2][2] + c[3][2])) * sc;
    const float lo2 = __shfl_down_sync(~0u, lo, 4), hi2 = __shfl_down_sync(~0u, hi, 4);
    if ((lane & 7) == 0) mb_put2(dst, pack2(lo, lo2), pack2(hi, hi2));
}

__global__ void __launch_bounds__(NTHR, 1) fused_kernel(const __grid_constant__ Params P) {
    extern __shared__ __align__(1024) unsigned char smem_raw[];
    const uint32_t SB = (uint32_t)__cvta_generic_to_shared(smem_raw);
    const int tid = threadIdx.x, warp = tid >> 5, lane = tid & 31;
    const int g = lane >> 2, t = lane & 3;
    const int cta = blockIdx.x, j = cta >> 2, r = cta & 3;
    const uint2 tab = P.tab[cta];
    const int u0 = tab.x & 1023, nu = (tab.x >> 10) & 15, k0 = (tab.x >> 14) & 511, nk = (tab.x >> 23) & 31;
    const int h7 = tab.y & 15, mb7 = (tab.y >> 4) & 7;
    const bool full = cta < 112;
    const int nb = (nk + 1) >> 1, nbg = nk >> 1;
    const int g_uk = full ? 2 : 0, g_kv = g_uk + 4, g_uv = g_kv + nbg, g_wo = g_uv + 4, g_gu = g_wo + 2, g_wd = g_gu + 2;
    auto BAR = [&](int i) -> uint32_t { return SB + OFF_BAR + 8 * i; };

    if (warp == 11) {
        const int W1 = P.W & 15, W2 = (P.W >> 4) & 15, W3 = (P.W >> 8) & 15, W4 = (P.W >> 12) & 15, ngroups = full ? g_wd + 1 : g_wo;
        int done = 0;
        unsigned long long pol;
        asm volatile("createpolicy.fractional.L2::evict_first.b64 %0, 1.0;" : "=l"(pol));
        if (lane < 8) asm volatile("prefetch.tensormap [%0];" ::"l"(reinterpret_cast<const char*>(&P) + lane * 128) : "memory");
#pragma unroll 1
        for (int gi = 0; gi < ngroups; gi++) {
            if (gi == min(W1, 4)) {
                if (lane == 0) {
                    for (int i = gi; i < 4; i++) mbar_init(BAR(i), 1);
                    asm volatile("fence.mbarrier_init.release.cluster;" ::: "memory");
                }
                __syncthreads();
                asm volatile("barrier.cluster.arrive.relaxed.aligned;" ::: "memory");
            }
            const CUtensorMap* map;
            uint32_t dst, dstep = UNIT;
            int n = 2, x0 = 0, y0, z0 = -1, x1 = 0, y1, z1 = 0, y2 = 0, z2 = 0, gate = -1, pvgate = 0;
            if (gi < g_uk) {
                map = &P.wq; dst = OFF_CKV + (14 + 2 * gi) * UNIT;
                y0 = mb7 * 64 + gi * 32; y1 = y0 + 16; z0 = z1 = h7 * 4;
            } else if (gi < g_kv || (gi >= g_uv && gi < g_wo)) {
                const bool uv = gi >= g_uv;
                const int i0 = 2 * (gi - (uv ? g_uv : g_uk)), u = u0 + i0;
                if (gi == g_uv) gate = G_QA;
                map = uv ? &P.wuv : &P.wuk; dst = OFF_WA + i0 * UNIT; n = i0 == 6 ? nu - 6 : 2;
                y0 = (u & 63) * 16; z0 = (u >> 6) * 4; y1 = ((u + 1) & 63) * 16; z1 = ((u + 1) >> 6) * 4;
                y2 = ((u + 2) & 63) * 16; z2 = ((u + 2) >> 6) * 4;
            } else if (gi < g_uv) {
                const int b = gi - g_kv;
                if (b == 7 && full) gate = G_P1;
                map = &P.ckv; dst = OFF_CKV + 2 * b * UNIT; n = b == nbg - 1 ? nk - 2 * b : 2;
                y0 = (k0 + 2 * b) * 16; y1 = y0 + 16; y2 = y0 + 32; z0 = z1 = z2 = r * 4;
            } else if (gi < g_gu) {
                const int i = gi - g_wo;
                pvgate = 1;
                map = &P.wo; dst = OFF_CKV + 2 * i * UNIT;
                x0 = x1 = mb7 * 64; y0 = h7 * 256 + i * 128; y1 = y0 + 64;
            } else if (gi < g_wd) {
                const int i = gi - g_gu;
                pvgate = 3;
                map = (r & 1) ? &P.wu : &P.wg; dst = OFF_CKV + 4 * UNIT + i * 14336; n = 1; dstep = 14336;
                x0 = j * 64; y0 = (r >> 1) * 224 + i * 112; y1 = 0;
            } else {
                pvgate = 4;
                map = &P.wd; dst = OFF_CKV + 8 * UNIT;
                x0 = r * 112; x1 = x0 + 64; y0 = y1 = j * 64;
            }
            if (gate >= 0) mbar_wait(BAR(gate), 0);
            if (pvgate) pv_wait(SB + OFF_PVC, pvgate);
            {
                const int W = gi < g_kv ? W1 : gi < g_uv ? W2 : gi < g_wo ? W3 : W4;
#pragma unroll 1
                for (; done <= gi - W; done++) mbar_wait(BAR(done), 0);
            }
            if (lane == 0) {
                const uint32_t bar = BAR(gi);
                if (gi < min(W1, 4)) {
                    mbar_init(bar, 1);
                    asm volatile("fence.mbarrier_init.release.cluster;" ::: "memory");
                }
                mbar_expect(bar, n * dstep);
                if (z0 >= 0) {
                    tma3p(SB + dst, map, 0, y0, z0, bar, pol);
                    tma3p(SB + dst + UNIT, map, 0, y1, z1, bar, pol);
                    if (n > 2) tma3p(SB + dst + 2 * UNIT, map, 0, y2, z2, bar, pol);
                } else {
                    tma2p(SB + dst, map, x0, y0, bar, pol);
                    if (n > 1) tma2p(SB + dst + UNIT, map, x1, y1, bar, pol);
                }
                if (gi == g_kv) TRACE(15);
                if (gi == g_uv) TRACE(19);
                if (gi == g_wo) TRACE(20);
            }
            __syncwarp();
        }
        if (lane == 0) TRACE(31);
        asm volatile("barrier.cluster.wait.acquire.aligned;" ::: "memory");
        return;
    }

    uint32_t epoch, xr[7], xa[8], xw0, xw1;
    {
        const uint32_t* x32 = reinterpret_cast<const uint32_t*>(P.x);
        asm volatile("ld.relaxed.gpu.global.u32 %0, [%1];" : "=r"(epoch) : "l"(&g_epoch) : "memory");
#pragma unroll
        for (int i = 0; i < 7; i++) xr[i] = ldg_early(x32 + lane + 32 * i);
#pragma unroll
        for (int i = 0; i < 8; i++) xa[i] = ldg_early(x32 + mb7 * 32 + (i >> 1) * 8 + (i & 1) * 4 + t);
        xw0 = ldg_early(x32 + r * 56 + 2 * min(lane, 27));
        xw1 = ldg_early(x32 + r * 56 + 2 * min(lane, 27) + 1);
    }
    if (lane == 0) {
#pragma unroll 1
        for (int i = 4 + (warp > 11 ? warp - 1 : warp); i < NBARS; i += 15) mbar_init(BAR(i), i == G_P1 ? 8 : i == G_QA ? 4 : i == B_GU ? 2 : 1);
        if (warp >= 8 && warp < 11) sts128(SB + OFF_REF + (warp - 8) * 16, make_uint4(0, 0, 0, 0));
        if (warp >= 12) sts128(SB + OFF_PVC + (warp - 12) * 16, make_uint4(0, 0, 0, 0));
        asm volatile("fence.mbarrier_init.release.cluster;" ::: "memory");
    }
    __syncthreads();
    asm volatile("barrier.cluster.arrive.relaxed.aligned;" ::: "memory");
    const int NC = P.NC;
    const int hA = u0 >> 6, hB = (u0 + nu - 1) >> 6;
    const int RS = P.RS, RP = RS + 1;
    const uint32_t xoff = nk <= 17 ? OFF_CKV + 17 * UNIT : OFF_WA + 8 * UNIT;
    auto slot_off = [&](int i) -> uint32_t { return i < 3 ? OFF_SLOT + i * 2048 : xoff + (i - 3) * 2048; };
    auto p_off = [&](int i) -> uint32_t { return i < 4 ? OFF_PBUF + i * PSTRIDE : xoff + 4096 + (i - 4) * PSTRIDE; };

    if (warp >= 12) {
        const int nt = warp - 12;
        const uint32_t s_dst = mapa(SB + r * 512 + (nt * 2 + (g >> 2)) * 64 + t * 16, g & 3);
        const uint32_t s_bar = mapa(BAR(B_S0), g & 3);
        const int srow = (nt & 1) * 8 + (lane & 7);
        const uint32_t s_src0 = SB + OFF_CKV + (nt >> 1) * UNIT + srow * 128 + (((lane >> 3) ^ (srow & 7)) << 4);
        const uint32_t s_src1 = SB + OFF_CKV + (nt >> 1) * UNIT + srow * 128 + (((4 + (lane >> 3)) ^ (srow & 7)) << 4);
        unsigned char* const mb = g_mb + (epoch & 1) * MB_SET;
        const int ht = tid - 384;
        bar_sync(13, 384);
        delay((P.dly & 31) * 64);
        if (ht < 64 || hB != hA) {
            const int i = ht & 63, hs = ht >> 6;
            uint4 v[7];
            mb_poll<7, 1024>(mb + MB1 + (hs ? hB : hA) * 7168 + i * 16, 7, v);
            float a0 = 0.f, a1 = 0.f, a2 = 0.f, a3 = 0.f;
#pragma unroll
            for (int k = 0; k < 7; k++) {
                a0 += __uint_as_float(v[k].x); a1 += __uint_as_float(v[k].y);
                a2 += __uint_as_float(v[k].z); a3 += __uint_as_float(v[k].w);
            }
            const uint32_t d = SB + OFF_QST + hs * 512 + frag_off(2 * i);
            sts32(d, pack2(a0, a1));
            sts32(d + 16, pack2(a2, a3));
        }
        asm volatile("bar.arrive 7, 416;" ::: "memory");
        asm volatile("barrier.cluster.wait.acquire.aligned;" ::: "memory");
        {
            bar_sync(6, 416);
            delay(((P.dly >> 5) & 31) * 64);
            uint4 v[4];
            mb_poll<4, 2048>(mb + MB2 + r * 8192 + ht * 16, 4, v);
            const uint32_t a = SB + OFF_WA + ((ht >> 1) & 15) * 512 + ((ht >> 5) * 4 + (ht & 1) * 2) * 16;
            sts128(a, make_uint4(v[0].x, v[2].x, v[0].y, v[2].y));
            sts128(a + 16, make_uint4(v[0].z, v[2].z, v[0].w, v[2].w));
            sts128(a + 256, make_uint4(v[1].x, v[3].x, v[1].y, v[3].y));
            sts128(a + 272, make_uint4(v[1].z, v[3].z, v[1].w, v[3].w));
            bar_sync(9, 128);
        }
        if (ht == 0) TRACE(4);
        uint32_t qa[16][4];
#pragma unroll
        for (int s = 0; s < 16; s++) {
            const uint4 q = lds128(SB + OFF_WA + s * 512 + lane * 16);
            qa[s][0] = q.x; qa[s][1] = q.y; qa[s][2] = q.z; qa[s][3] = q.w;
        }
        __syncwarp();
        if (lane == 0) mbar_arrive(BAR(G_QA));
        const int nbs = (nk - (nt >> 1) + 1) >> 1;
        int sb = 0;
        bool landed = false;
#pragma unroll 1
        for (int b = 0; b < nbs; b++) {
            if (!landed) mbar_wait(BAR(g_kv + b), 0);
            float c0[4] = {}, c1[4] = {}, c2[4] = {}, c3[4] = {};
#pragma unroll
            for (int i = 0; i < 4; i++) {
                uint32_t b0, b1, b2, b3, b4, b5, b6, b7;
                ldsm4(s_src0 + 2 * b * UNIT + i * 2048, b0, b1, b2, b3);
                ldsm4(s_src1 + 2 * b * UNIT + i * 2048, b4, b5, b6, b7);
                mma16816(c0, qa[4 * i][0], qa[4 * i][1], qa[4 * i][2], qa[4 * i][3], b0, b1);
                mma16816(c1, qa[4 * i + 1][0], qa[4 * i + 1][1], qa[4 * i + 1][2], qa[4 * i + 1][3], b2, b3);
                mma16816(c2, qa[4 * i + 2][0], qa[4 * i + 2][1], qa[4 * i + 2][2], qa[4 * i + 2][3], b4, b5);
                mma16816(c3, qa[4 * i + 3][0], qa[4 * i + 3][1], qa[4 * i + 3][2], qa[4 * i + 3][3], b6, b7);
            }
            landed = b + 1 >= nbg || mbar_test(BAR(g_kv + b + 1), 0);
            if (b >= RS) pv_wait(SB + OFF_PVC, b - RS);
            st_async_v4(s_dst + slot_off(sb), __float_as_uint((c0[0] + c1[0]) + (c2[0] + c3[0])),
                        __float_as_uint((c0[1] + c1[1]) + (c2[1] + c3[1])), __float_as_uint((c0[2] + c1[2]) + (c2[2] + c3[2])),
                        __float_as_uint((c0[3] + c1[3]) + (c2[3] + c3[3])), s_bar + sb * 8);
            if (++sb == RS) sb = 0;
        }
        if (!full) return;
        if (nt < 2) {
            bar_sync(10, 320);
            delay(((P.dly >> 15) & 31) * 64);
            uint4 v[10];
            mb_poll<10, 1024>(mb + MB4 + h7 * 12288 + ht * 16, (tab.y >> 16) & 15, v);
            float a0 = 0.f, a1 = 0.f, a2 = 0.f, a3 = 0.f, e0 = 0.f, e1 = 0.f, e2 = 0.f, e3 = 0.f;
#pragma unroll
            for (int k = 0; k < 5; k++) {
                a0 += __uint_as_float(v[k].x); a1 += __uint_as_float(v[k].y);
                a2 += __uint_as_float(v[k].z); a3 += __uint_as_float(v[k].w);
                e0 += __uint_as_float(v[5 + k].x); e1 += __uint_as_float(v[5 + k].y);
                e2 += __uint_as_float(v[5 + k].z); e3 += __uint_as_float(v[5 + k].w);
            }
            bar_sync(4, 96);
            const float rl = __uint_as_float(lds32(SB + OFF_MISC));
            const uint32_t d = SB + OFF_CTX + frag_off(2 * ht);
            sts32(d, pack2((a0 + e0) * rl, (a1 + e1) * rl));
            sts32(d + 16, pack2((a2 + e2) * rl, (a3 + e3) * rl));
            asm volatile("bar.arrive 8, 320;" ::: "memory");
        } else if (nt == 2) {
            bar_sync(11, 288);
            delay(((P.dly >> 20) & 31) * 64);
            if (lane < 28) {
                const int w = (r & 1) * 56 + 2 * lane;
                const uint32_t d0 = SB + OFF_H + (r >> 1) * 448 + frag_off(w);
                uint32_t da[4], ba[4];
#pragma unroll
                for (int k = 0; k < 4; k++) { da[k] = mapa(d0, k); ba[k] = mapa(BAR(B_H), k); }
                uint4 v[16];
                mb_poll<16, 1792>(mb + MB5 + r * 448 + lane * 16, 16, v);
                float a[4][4] = {};
#pragma unroll
                for (int k = 0; k < 16; k++) {
                    a[k & 3][0] += __uint_as_float(v[k].x); a[k & 3][1] += __uint_as_float(v[k].y);
                    a[k & 3][2] += __uint_as_float(v[k].z); a[k & 3][3] += __uint_as_float(v[k].w);
                }
                const uint32_t h0 = pack2(bflo(xw0) + bf16r((a[0][0] + a[1][0]) + (a[2][0] + a[3][0])),
                                          bfhi(xw0) + bf16r((a[0][1] + a[1][1]) + (a[2][1] + a[3][1])));
                const uint32_t h1 = pack2(bflo(xw1) + bf16r((a[0][2] + a[1][2]) + (a[2][2] + a[3][2])),
                                          bfhi(xw1) + bf16r((a[0][3] + a[1][3]) + (a[2][3] + a[3][3])));
#pragma unroll
                for (int k = 0; k < 4; k++) {
                    st_async_b32(da[k], h0, ba[k]);
                    st_async_b32(da[k] + 16, h1, ba[k]);
                }
            }
        } else {
            const int k = (lane >> 1) & 3;
            mbar_wait_cl(BAR(B_H), 0);
            {
                float v[14], mean, den;
#pragma unroll
                for (int i = 0; i < 7; i++) {
                    const uint32_t w = lds32(SB + OFF_H + (lane + 32 * i) * 4);
                    v[2 * i] = bflo(w); v[2 * i + 1] = bfhi(w);
                }
                ln_stats1(v, bflo(lds32(SB + OFF_H)), mean, den);
                if (lane == 0) {
                    sts32(SB + OFF_MISC + 8, __float_as_uint(mean));
                    sts32(SB + OFF_MISC + 12, __float_as_uint(__fdividef(1.f, den)));
                    mbar_arrive(BAR(B_GU));
                }
            }
            const uint32_t hw = lds32(SB + OFF_H + (r >> 1) * 448 + frag_off((r & 1) * 56 + j * 2 + (k >> 1)));
            uint4 v[4];
            const int n = lane < 4 ? 4 : lane < 8 ? 3 : 0;
            bar_sync(12, 288);
            delay(((P.dly >> 25) & 31) * 64);
            mb_poll<4, 256>(mb + MB6 + ((r * 28 + j) * 28 + lane) * 32, n, v);
            float v0 = (__uint_as_float(v[0].x) + __uint_as_float(v[1].x)) + (__uint_as_float(v[2].x) + __uint_as_float(v[3].x));
            float v1 = (__uint_as_float(v[0].y) + __uint_as_float(v[1].y)) + (__uint_as_float(v[2].y) + __uint_as_float(v[3].y));
            float v2 = (__uint_as_float(v[0].z) + __uint_as_float(v[1].z)) + (__uint_as_float(v[2].z) + __uint_as_float(v[3].z));
            float v3 = (__uint_as_float(v[0].w) + __uint_as_float(v[1].w)) + (__uint_as_float(v[2].w) + __uint_as_float(v[3].w));
            __syncwarp();
            const bool up = lane & 4;
            const float s0 = up ? v0 : v2, s1 = up ? v1 : v3;
            const float k0v = up ? v2 : v0, k1v = up ? v3 : v1;
            v0 = k0v + __shfl_xor_sync(~0u, s0, 4);
            v1 = k1v + __shfl_xor_sync(~0u, s1, 4);
            const bool up2 = lane & 2;
            const float s2 = up2 ? v0 : v1, k2v = up2 ? v1 : v0;
            v0 = k2v + __shfl_xor_sync(~0u, s2, 2);
            v0 += __shfl_xor_sync(~0u, v0, 1);
            if (lane < 8 && (lane & 1) == 0)
                P.out[r * 112 + j * 4 + k] = __float2bfloat16_rn(((k & 1) ? bfhi(hw) : bflo(hw)) + bf16r(v0));
            if (cta == 0 && lane == 0) g_epoch = epoch + 1;
            if (lane == 0) TRACE(13);
        }
        return;
    }
    if (warp >= 8) {
        const int sb = warp - 8, nt = lane >> 3, gg = (lane >> 2) & 1;
        if (lane == 0) {
            mbar_expect(BAR(B_S0 + sb), 2048);
            if (sb + 3 < RS) mbar_expect(BAR(B_S0 + sb + 3), 2048);
        }
        const uint32_t dst_a = mapa(SB + (nt >> 1) * 512 + ((r + 4 * gg) * 4 + t) * 16, (nt & 1) * 2);
        const uint32_t dst_b = mapa(SB + (nt >> 1) * 512 + ((r + 4 * gg) * 4 + t) * 16, (nt & 1) * 2 + 1);
        const uint32_t bar_a = mapa(BAR(B_P0), (nt & 1) * 2), bar_b = mapa(BAR(B_P0), (nt & 1) * 2 + 1);
        const uint32_t dst_m = mapa(SB + 1024 + (r + 4 * gg + 8 * nt) * 4, t), bar_m = mapa(BAR(B_P0), t);
        const uint32_t ref_prev = SB + OFF_REF + (sb == 0 ? 2 : sb - 1) * 16;
        if (sb == 0) {
            const int ub = u0 + 8;
            const uint32_t o2b = MB2 + ((((ub & 63) >> 4) * 16 + (ub >> 6)) * 16 + (ub & 15)) * 32 + (lane >> 3) * 8;
            if (nu > 8 && (lane & 7) == 0) mb_clear2(o2b);
            bar_sync(7, 416);
            if (nu > 8) qabs_unit(SB, g_mb + (epoch & 1) * MB_SET + o2b, 8, (ub >> 6) != hA, BAR(g_uk + 3), lane);
            asm volatile("bar.arrive 6, 416;" ::: "memory");
        }
        asm volatile("barrier.cluster.wait.acquire.aligned;" ::: "memory");
#pragma unroll 1
        for (int b = sb; b < nb; b += 3) {
            const int si = b >= RS ? (b >= 2 * RS ? b - 2 * RS : b - RS) : b, sph = (b >= RS && b < 2 * RS) ? 1 : 0;
            const int pi = b >= RP ? (b >= 2 * RP ? b - 2 * RP : b - RP) : b;
            const uint32_t po = p_off(pi), bo = pi * 8, sa = SB + slot_off(si) + lane * 16;
            const bool valid = 2 * b + (nt >> 1) < nk;
            if (b >= RS) {
                const uint32_t tk = SB + OFF_REF + ((b - RS) % 3) * 16;
#pragma unroll 1
                for (int it = 0; it < SPIN_LIMIT * 8; it++)
                    if ((int)(lds128_vol(tk).x & 15u) > b - RS) break;
            }
            mbar_wait_cl(BAR(B_S0 + si), sph);
            if (lane == 0 && b == 5) TRACE(16);
            const uint4 v0 = lds128(sa), v1 = lds128(sa + 512), v2 = lds128(sa + 1024), v3 = lds128(sa + 1536);
            float s0 = (__uint_as_float(v0.x) + __uint_as_float(v1.x)) + (__uint_as_float(v2.x) + __uint_as_float(v3.x));
            float s1 = (__uint_as_float(v0.y) + __uint_as_float(v1.y)) + (__uint_as_float(v2.y) + __uint_as_float(v3.y));
            float s2 = (__uint_as_float(v0.z) + __uint_as_float(v1.z)) + (__uint_as_float(v2.z) + __uint_as_float(v3.z));
            float s3 = (__uint_as_float(v0.w) + __uint_as_float(v1.w)) + (__uint_as_float(v2.w) + __uint_as_float(v3.w));
            const int i0 = valid ? f2o(fmaxf(s0, s1)) : INT_MIN, i1 = valid ? f2o(fmaxf(s2, s3)) : INT_MIN;
            int ra = __reduce_max_sync(~0u, gg ? INT_MIN : i0), rb = __reduce_max_sync(~0u, gg ? i0 : INT_MIN);
            int rc = __reduce_max_sync(~0u, gg ? INT_MIN : i1), rd = __reduce_max_sync(~0u, gg ? i1 : INT_MIN);
            ra = (ra + 15) & ~15; rb = (rb + 15) & ~15; rc = (rc + 15) & ~15; rd = (rd + 15) & ~15;
            if (b > 0) {
                uint4 pr;
#pragma unroll 1
                for (int it = 0; it < SPIN_LIMIT * 8; it++) {
                    pr = lds128_vol(ref_prev);
                    if ((int)(pr.x & pr.y & pr.z & pr.w & 15u) == b && (int)((pr.x | pr.y | pr.z | pr.w) & 15u) == b) break;
                }
                ra = max(ra, (int)pr.x - b); rb = max(rb, (int)pr.y - b); rc = max(rc, (int)pr.z - b); rd = max(rd, (int)pr.w - b);
            }
            __syncwarp();
            if (lane == 0) sts128_vol(SB + OFF_REF + sb * 16, make_uint4(ra | (b + 1), rb | (b + 1), rc | (b + 1), rd | (b + 1)));
            const float n0 = o2f(gg ? rb : ra), n1 = o2f(gg ? rd : rc);
            const uint32_t w0 = pack2(ex2(s0 - n0), ex2(s1 - n0)), w1 = pack2(ex2(s2 - n1), ex2(s3 - n1));
            const uint32_t o0 = __shfl_xor_sync(~0u, w0, 8), o1 = __shfl_xor_sync(~0u, w1, 8);
            if (lane < 16) st_async_b32(dst_m + po, __float_as_uint(nt ? n1 : n0), bar_m + bo);
            if (valid) {
                const bool odd = nt & 1;
                const uint32_t x0 = odd ? o0 : w0, x1 = odd ? o1 : w1, x2 = odd ? w0 : o0, x3 = odd ? w1 : o1;
                st_async_v4(dst_a + po, x0, x1, x2, x3, bar_a + bo);
                st_async_v4(dst_b + po, x0, x1, x2, x3, bar_b + bo);
            }
            if (lane == 0 && b == 5) TRACE(17);
            if (lane == 0 && b + RS < nb) mbar_expect(BAR(B_S0 + si), (2 * (b + RS) + 1 < nk) ? 2048 : 1024);
        }
        bar_sync(5, 352);
        delay(((P.dly >> 10) & 31) * 64);
        const unsigned char* mbp = g_mb + (epoch & 1) * MB_SET;
        if (sb == 2) {
            const unsigned char* src = mbp + MB3 + (u0 + 8) * 1024 + lane * 16;
            const int n = nu > 8 ? ((16 + (lane >> 1) < NC) ? 2 : 1) : 0;
            uint4 v[2];
            mb_first<2, 512>(src, n, v);
            combine_unit(SB, src, n, v, 8, 8 < (hA + 1) * 64 - u0, lane);
            asm volatile("bar.arrive 3, 288;" ::: "memory");
        } else {
#pragma unroll 1
            for (int pass = 0; pass < ((sb == 0 && full) ? 2 : 1); pass++) {
                const unsigned char* pm = mbp + MBM + ((pass ? h7 : sb ? hB : hA) * NC_MAX + lane) * 32;
                uint2 a = make_uint2(0xff800000u, 0);
                if (lane < NC) {
#pragma unroll 1
                    for (int it = 0; it < SPIN_LIMIT; it++) {
                        asm volatile("{.reg .b64 t; ld.relaxed.gpu.global.b64 t, [%2]; mov.b64 {%0,%1}, t;}" : "=r"(a.x), "=r"(a.y) : "l"(pm) : "memory");
                        if (a.x != 0u) break;
                    }
                }
                __syncwarp();
                const float mj = __uint_as_float(a.x);
                const float w = ex2(mj - o2f(__reduce_max_sync(~0u, f2o(mj))));
                if (pass == 0) {
                    const int jj = lane & 15;
                    const uint32_t d = SB + OFF_WGT + sb * 128 + ((lane >> 4) * 4 + ((jj & 7) >> 1)) * 16 + (jj >> 3) * 8 + (jj & 1) * 2;
                    const __nv_bfloat16 hi = __float2bfloat16_rn(w), lo = __float2bfloat16_rn(w - __bfloat162float(hi));
                    sts16(d, *reinterpret_cast<const uint16_t*>(&hi));
                    sts16(d + 4, *reinterpret_cast<const uint16_t*>(&lo));
                    asm volatile("bar.arrive 2, 352;" ::: "memory");
                } else {
                    float L = w * __uint_as_float(a.y);
#pragma unroll
                    for (int o = 16; o; o >>= 1) L += __shfl_xor_sync(~0u, L, o);
                    if (lane == 0) sts32(SB + OFF_MISC, __float_as_uint(__fdividef(1.f, L)));
                    asm volatile("bar.arrive 4, 96;" ::: "memory");
                }
            }
        }
        return;
    }

    if (tid == 0) {
#pragma unroll 1
        for (int i = 0; i < RP; i++) mbar_expect(BAR(B_P0 + i), 1088);
        mbar_expect(BAR(B_H), 896);
        mbar_expect(BAR(B_GU), 2048);
    }
    const uint32_t o1 = MB1 + cta * 1024 + warp * 128 + lane * 8;
    const uint32_t o3 = MB3 + ((g * 64 + r * 16 + warp * 2) * NC_MAX + j) * 32 + t * 8;
    const bool a4 = g < 4 || hB != hA;
    const uint32_t o4 = MB4 + ((g < 4 ? hA : hB) * 12 + ((tab.y >> (g < 4 ? 8 : 12)) & 15)) * 1024 + warp * 128 + (lane & 15) * 8;
    const uint32_t o5 = MB5 + h7 * 1792 + mb7 * 256 + warp * 32 + t * 8;
    const int li6 = (warp + 8 * (g & 1)) * 4 + t;
    const bool a6 = g < 4 && ((g & 1) == 0 || warp < 6);
    const uint32_t o6 = MB6 + ((r * 28 + (li6 >> 1)) * 28 + j) * 32 + (g >> 1) * 16 + (li6 & 1) * 8;
    const bool am = tid < 32 && (g & 3) == r;
    const uint32_t om = MBM + (g * NC_MAX + j) * 32 + t * 8;
    const int ua = u0 + warp;
    const uint32_t o2a = MB2 + ((((ua & 63) >> 4) * 16 + (ua >> 6)) * 16 + (ua & 15)) * 32 + (lane >> 3) * 8;
    if (full && lane < 16) mb_clear2(o1);
    if ((lane & 7) == 0) mb_clear2(o2a);
    unsigned char* const mb = g_mb + (epoch & 1) * MB_SET;

    if (full) {
        float v[14];
#pragma unroll
        for (int i = 0; i < 7; i++) { v[2 * i] = bflo(xr[i]); v[2 * i + 1] = bfhi(xr[i]); }
        float mean, den;
        ln_stats(v, mean, den);
        const float rden = __frcp_rn(den);
#pragma unroll
        for (int i = 0; i < 8; i++) xa[i] = pack2(ln_apply_r(bflo(xa[i]), mean, rden), ln_apply_r(bfhi(xa[i]), mean, rden));
        if (tid == 0) TRACE(14);
        float acc[4][4] = {};
        const int row = (lane & 7) + (lane & 8), ch = (warp & 1) * 4 + (lane >> 4);
        const uint32_t a0 = SB + OFF_CKV + 14 * UNIT + (warp >> 1) * 2048 + row * 128;
#pragma unroll
        for (int s = 0; s < 4; s++) {
            if ((s & 1) == 0) mbar_wait(BAR(s >> 1), 0);
            uint32_t b0, b1, b2, b3, b4, b5, b6, b7;
            ldsm4t(a0 + s * UNIT + ((ch ^ (row & 7)) << 4), b0, b1, b2, b3);
            ldsm4t(a0 + s * UNIT + (((ch + 2) ^ (row & 7)) << 4), b4, b5, b6, b7);
            mma16816(acc[0], xa[2 * s], 0, xa[2 * s + 1], 0, b0, b1);
            mma16816(acc[1], xa[2 * s], 0, xa[2 * s + 1], 0, b2, b3);
            mma16816(acc[2], xa[2 * s], 0, xa[2 * s + 1], 0, b4, b5);
            mma16816(acc[3], xa[2 * s], 0, xa[2 * s + 1], 0, b6, b7);
        }
        const float v0 = (g & 2) ? ((g & 1) ? acc[3][0] : acc[2][0]) : ((g & 1) ? acc[1][0] : acc[0][0]);
        const float v1 = (g & 2) ? ((g & 1) ? acc[3][1] : acc[2][1]) : ((g & 1) ? acc[1][1] : acc[0][1]);
        if (lane < 16) mb_put2f(mb + o1, v0, v1);
        __syncwarp();
        if (lane == 0) mbar_arrive(BAR(G_P1));
    }
    asm volatile("bar.arrive 13, 384;" ::: "memory");
    if (tid == 0) TRACE(1);
    mb_clear2(o3); mb_clear2(o3 + 1024); mb_clear2(o3 + 524288); mb_clear2(o3 + 524288 + 1024);
    if (a4) mb_clear2(o4);
    if (am) { mb_clear2(om); mb_clear2(om + 8 * NC_MAX * 32); }
    if (full) {
        if (lane < 4) mb_clear2(o5);
        if (a6) mb_clear2(o6);
    }
    bar_sync(7, 416);
    if (tid == 0) TRACE(2);
    qabs_unit(SB, mb + o2a, warp, (ua >> 6) != hA, BAR(g_uk + (warp >> 1)), lane);
    if (tid == 0) TRACE(3);
    asm volatile("bar.arrive 6, 416;" ::: "memory");
    asm volatile("barrier.cluster.wait.acquire.aligned;" ::: "memory");
    {
        float acc[4][4] = {};
        float mr0 = -INFINITY, mr1 = -INFINITY, tl[4] = {};
        const int prow = (lane & 7) + (lane & 8), pch = (warp & 1) * 4 + (lane >> 4);
        const uint32_t p_src0 = SB + OFF_CKV + (warp >> 1) * 2048 + prow * 128 + ((pch ^ (prow & 7)) << 4);
        const uint32_t p_src1 = SB + OFF_CKV + (warp >> 1) * 2048 + prow * 128 + (((pch + 2) ^ (prow & 7)) << 4);
        const uint32_t one = 0x3f803f80u;
#pragma unroll 1
        for (int b = 0, pb = 0, pph = 0; b < nb; b++) {
            const bool two = 2 * b + 1 < nk;
            const uint32_t pbase = SB + p_off(pb);
            mbar_wait_cl(BAR(B_P0 + pb), pph);
            if (tid == 0) TRACE(21 + b);
            uint32_t b0[8], b1[8];
            const float mb0 = __uint_as_float(lds32(pbase + 1024 + g * 4));
            const float mb1 = __uint_as_float(lds32(pbase + 1024 + 32 + g * 4));
            const uint4 p0 = lds128(pbase + lane * 16);
            ldsm4t(p_src0 + 2 * b * UNIT, b0[0], b0[1], b0[2], b0[3]);
            ldsm4t(p_src1 + 2 * b * UNIT, b0[4], b0[5], b0[6], b0[7]);
            uint4 p1;
            if (two) {
                p1 = lds128(pbase + 512 + lane * 16);
                ldsm4t(p_src0 + (2 * b + 1) * UNIT, b1[0], b1[1], b1[2], b1[3]);
                ldsm4t(p_src1 + (2 * b + 1) * UNIT, b1[4], b1[5], b1[6], b1[7]);
            }
            if (__any_sync(~0u, mb0 != mr0 || mb1 != mr1)) {
                const float al0 = ex2(mr0 - mb0), al1 = ex2(mr1 - mb1);
                mr0 = mb0; mr1 = mb1;
#pragma unroll
                for (int i = 0; i < 4; i++) { acc[i][0] *= al0; acc[i][1] *= al0; acc[i][2] *= al1; acc[i][3] *= al1; }
                tl[0] *= al0; tl[2] *= al1;
            }
#pragma unroll
            for (int i = 0; i < 4; i++) mma16816(acc[i], p0.x, p0.y, p0.z, p0.w, b0[2 * i], b0[2 * i + 1]);
            mma16816(tl, p0.x, p0.y, p0.z, p0.w, one, one);
            if (two) {
#pragma unroll
                for (int i = 0; i < 4; i++) mma16816(acc[i], p1.x, p1.y, p1.z, p1.w, b1[2 * i], b1[2 * i + 1]);
                mma16816(tl, p1.x, p1.y, p1.z, p1.w, one, one);
            }
            if (tid == 0 && b + RP < nb) mbar_expect(BAR(B_P0 + pb), (2 * (b + RP) + 1 < nk) ? 1088 : 576);
            __syncwarp();
            if (lane == 0) red_add_rel(SB + OFF_PVC + b * 4, 1);
            if (++pb == RP) { pb = 0; pph ^= 1; }
        }
        if (am) {
            mb_put2f(mb + om, mr0, tl[0]);
            mb_put2f(mb + om + 8 * NC_MAX * 32, mr1, tl[2]);
        }
        mb_put2(mb + o3, pack2(acc[0][0], acc[0][1]), pack2(acc[1][0], acc[1][1]));
        mb_put2(mb + o3 + 1024, pack2(acc[2][0], acc[2][1]), pack2(acc[3][0], acc[3][1]));
        mb_put2(mb + o3 + 524288, pack2(acc[0][2], acc[0][3]), pack2(acc[1][2], acc[1][3]));
        mb_put2(mb + o3 + 524288 + 1024, pack2(acc[2][2], acc[2][3]), pack2(acc[3][2], acc[3][3]));
    }
    if (tid == 0) TRACE(5);
    {
        const uint32_t tpub = clock();
        const unsigned char* psrc = mb + MB3 + ua * 1024 + lane * 16;
        const int pn = (16 + (lane >> 1) < NC) ? 2 : 1;
        bar_sync(5, 352);
        uint32_t wb[9][8];
        const int p = (lane & 7) + (lane & 8);
        const int prow = ((p >> 1) & 1) * 8 + (p >> 2) * 2 + (p & 1), pch = (warp & 1) * 4 + (lane >> 4);
        const uint32_t src0 = SB + OFF_WA + (warp >> 1) * 2048 + prow * 128 + ((pch ^ (prow & 7)) << 4);
        const uint32_t src1 = SB + OFF_WA + (warp >> 1) * 2048 + prow * 128 + (((pch + 2) ^ (prow & 7)) << 4);
        uint4 pv[2];
#pragma unroll
        for (int ul = 0; ul < 9; ul++) {
            const uint32_t uo = (ul < 8 || nu > 8) ? ul * UNIT : 0;
            if ((ul & 1) == 0 && ul < 8) mbar_wait(BAR(g_uv + (ul >> 1)), 0);
            ldsm4t(src0 + uo, wb[ul][0], wb[ul][1], wb[ul][2], wb[ul][3]);
            ldsm4t(src1 + uo, wb[ul][4], wb[ul][5], wb[ul][6], wb[ul][7]);
        }
        while (clock() - tpub < ((P.dly >> 10) & 31) * 64) {}
        mb_first<2, 512>(psrc, pn, pv);
        if (tid == 0) TRACE(18);
        const int nA = (hA + 1) * 64 - u0;
        combine_unit(SB, psrc, pn, pv, warp, warp < nA, lane);
        bar_sync(3, 288);
        if (tid == 0) TRACE(6);
        float acc[2][4][4] = {};
#pragma unroll
        for (int ul = 0; ul < 9; ul++) {
            const uint4 a = lds128((ul < nA) == (g < 4) ? SB + OFF_AFR + ul * 64 + t * 16 : SB + OFF_PVC + 48);
#pragma unroll
            for (int i = 0; i < 4; i++) mma16816(acc[ul & 1][i], a.x, a.y, a.z, a.w, wb[ul][2 * i], wb[ul][2 * i + 1]);
        }
        float v0, v1;
        {
            const int i = g & 3;
            float e[4][2];
#pragma unroll
            for (int k = 0; k < 4; k++) {
                e[k][0] = (acc[0][k][0] + acc[0][k][2]) + (acc[1][k][0] + acc[1][k][2]);
                e[k][1] = (acc[0][k][1] + acc[0][k][3]) + (acc[1][k][1] + acc[1][k][3]);
            }
            v0 = (i & 2) ? ((i & 1) ? e[3][0] : e[2][0]) : ((i & 1) ? e[1][0] : e[0][0]);
            v1 = (i & 2) ? ((i & 1) ? e[3][1] : e[2][1]) : ((i & 1) ? e[1][1] : e[0][1]);
        }
        if (a4) mb_put2f(mb + o4, v0, v1);
    }
    if (tid == 0) TRACE(7);
    if (!full) return;
    asm volatile("bar.arrive 10, 320;" ::: "memory");

    {
        mbar_wait(BAR(g_wo), 0);
        mbar_wait(BAR(g_wo + 1), 0);
        uint32_t b[8][4];
        const uint32_t src = SB + OFF_CKV + lane * 128 + ((warp ^ (lane & 7)) << 4);
#pragma unroll
        for (int s2 = 0; s2 < 8; s2++) ldsm4t(src + s2 * 4096, b[s2][0], b[s2][1], b[s2][2], b[s2][3]);
        bar_sync(8, 320);
        if (tid == 0) TRACE(8);
        float c[4][4] = {};
#pragma unroll
        for (int s2 = 0; s2 < 8; s2++) {
            const uint4 a = lds128(SB + OFF_CTX + s2 * 64 + t * 16);
            mma16816(c[(s2 & 1) * 2], a.x, 0, a.y, 0, b[s2][0], b[s2][1]);
            mma16816(c[(s2 & 1) * 2 + 1], a.z, 0, a.w, 0, b[s2][2], b[s2][3]);
        }
        if (lane < 4) mb_put2f(mb + o5, (c[0][0] + c[1][0]) + (c[2][0] + c[3][0]), (c[0][1] + c[1][1]) + (c[2][1] + c[3][1]));
    }
    asm volatile("bar.arrive 11, 288;" ::: "memory");
    if (tid == 0) TRACE(9);

    {
        mbar_wait(BAR(g_gu), 0);
        mbar_wait(BAR(g_gu + 1), 0);
        uint32_t b[7][4];
        const uint32_t src = SB + OFF_CKV + 4 * UNIT + lane * 128 + ((warp ^ (lane & 7)) << 4);
#pragma unroll
        for (int s2 = 0; s2 < 7; s2++) ldsm4t(src + s2 * 4096, b[s2][0], b[s2][1], b[s2][2], b[s2][3]);
        const uint32_t gdst = mapa(SB + OFF_GU + r * 512 + (warp * 4 + t) * 16, g & 3), gbar = mapa(BAR(B_GU), g & 3);
        mbar_wait_cl(BAR(B_H), 0);
        if (tid == 0) TRACE(10);
        float c[4][4] = {};
        const uint32_t one = 0x3f803f80u;
#pragma unroll
        for (int s2 = 0; s2 < 7; s2++) {
            const uint4 a = lds128(SB + OFF_H + (r >> 1) * 448 + s2 * 64 + t * 16);
            mma16816(c[(s2 & 1) * 2], a.x, one, a.y, one, b[s2][0], b[s2][1]);
            mma16816(c[(s2 & 1) * 2 + 1], a.z, one, a.w, one, b[s2][2], b[s2][3]);
        }
        if (g < 4)
            st_async_v4(gdst, __float_as_uint((c[0][0] + c[1][0]) + (c[2][0] + c[3][0])),
                        __float_as_uint((c[0][1] + c[1][1]) + (c[2][1] + c[3][1])), __float_as_uint((c[0][2] + c[1][2]) + (c[2][2] + c[3][2])),
                        __float_as_uint((c[0][3] + c[1][3]) + (c[2][3] + c[3][3])), gbar);
    }
    {
        mbar_wait(BAR(g_wd), 0);
        uint32_t b[4][4];
        const uint32_t src = SB + OFF_CKV + 8 * UNIT + lane * 128 + ((warp ^ (lane & 7)) << 4);
        ldsm4t(src, b[0][0], b[0][1], b[0][2], b[0][3]);
        ldsm4t(src + 4096, b[1][0], b[1][1], b[1][2], b[1][3]);
        ldsm4t(src + UNIT, b[2][0], b[2][1], b[2][2], b[2][3]);
        ldsm4t(src + UNIT + 4096, b[3][0], b[3][1], b[3][2], b[3][3]);
        mbar_wait_cl(BAR(B_GU), 0);
        if (tid == 0) TRACE(11);
        const uint32_t ga = SB + OFF_GU + (((g & 3) * 2 + (g >> 2)) * 4 + t) * 16;
        const uint4 p0 = lds128(ga), p1 = lds128(ga + 512), p2 = lds128(ga + 1024), p3 = lds128(ga + 1536);
        const float mean = __uint_as_float(lds32(SB + OFF_MISC + 8)), inv = __uint_as_float(lds32(SB + OFF_MISC + 12));
        const float g0 = bf16r(((__uint_as_float(p0.x) + __uint_as_float(p2.x)) - mean * (__uint_as_float(p0.z) + __uint_as_float(p2.z))) * inv);
        const float g1 = bf16r(((__uint_as_float(p0.y) + __uint_as_float(p2.y)) - mean * (__uint_as_float(p0.w) + __uint_as_float(p2.w))) * inv);
        const float u0v = bf16r(((__uint_as_float(p1.x) + __uint_as_float(p3.x)) - mean * (__uint_as_float(p1.z) + __uint_as_float(p3.z))) * inv);
        const float u1v = bf16r(((__uint_as_float(p1.y) + __uint_as_float(p3.y)) - mean * (__uint_as_float(p1.w) + __uint_as_float(p3.w))) * inv);
        const float s0 = bf16r(__fdividef(1.f, 1.f + __expf(-g0))), s1 = bf16r(__fdividef(1.f, 1.f + __expf(-g1)));
        const uint32_t hw = pack2(s0 * u0v, s1 * u1v);
        uint32_t a[8];
#pragma unroll
        for (int k = 0; k < 8; k++) a[k] = __shfl_sync(~0u, hw, k * 4 + t);
        float c0[4] = {}, c1[4] = {}, c2[4] = {}, c3[4] = {};
        mma16816(c0, a[0], 0, a[4], 0, b[0][0], b[0][1]);
        mma16816(c1, a[0], 0, a[4], 0, b[2][0], b[2][1]);
        mma16816(c2, a[1], 0, a[5], 0, b[0][2], b[0][3]);
        mma16816(c3, a[1], 0, a[5], 0, b[2][2], b[2][3]);
        mma16816(c0, a[2], 0, a[6], 0, b[1][0], b[1][1]);
        mma16816(c1, a[2], 0, a[6], 0, b[3][0], b[3][1]);
        mma16816(c2, a[3], 0, a[7], 0, b[1][2], b[1][3]);
        mma16816(c3, a[3], 0, a[7], 0, b[3][2], b[3][3]);
        if (a6) mb_put2f(mb + o6, (g & 1) ? c1[0] + c3[0] : c0[0] + c2[0], (g & 1) ? c1[1] + c3[1] : c0[1] + c2[1]);
    }
    asm volatile("bar.arrive 12, 288;" ::: "memory");
    if (tid == 0) TRACE(12);
}

__device__ float f_q[4096], f_qa[16 * 1024], f_s[16 * 8192], f_cc[64 * 16 * 1024], f_ctx[4096], f_h[448], f_hh[1792];

__device__ __forceinline__ void block_ln(const float* v  , float* o  ) {
    float a[14];
    const int lane = threadIdx.x & 31;
#pragma unroll
    for (int i = 0; i < 14; i++) a[i] = v[lane + 32 * i];
    float mb, den;
    ln_stats(a, mb, den);
    for (int i = threadIdx.x; i < 448; i += blockDim.x) o[i] = bf16r(ln_apply(v[i], mb, den));
    __syncthreads();
}
__global__ void fb_q(const __nv_bfloat16* x, const __nv_bfloat16* wq) {
    __shared__ float xs[448], xn[448];
    for (int i = threadIdx.x; i < 448; i += blockDim.x) xs[i] = __bfloat162float(x[i]);
    __syncthreads();
    block_ln(xs, xn);
    const int c = blockIdx.x * blockDim.x + threadIdx.x;
    float a = 0.f;
    for (int m = 0; m < 448; m++) a += xn[m] * __bfloat162float(wq[(size_t)m * 4096 + c]);
    f_q[c] = bf16r(a);
}
__global__ void fb_qabs(const __nv_bfloat16* wuk) {
    const int row = blockIdx.x * 8 + (threadIdx.x >> 5), lane = threadIdx.x & 31;
    const int h = row & 15, c = row >> 4;
    float a = 0.f;
    for (int d = lane; d < 256; d += 32) a += f_q[h * 256 + d] * __bfloat162float(wuk[(size_t)row * 256 + d]);
    for (int o = 16; o; o >>= 1) a += __shfl_xor_sync(~0u, a, o);
    if (lane == 0) f_qa[h * 1024 + c] = a * 0.0625f;
}
__global__ void fb_scores(const __nv_bfloat16* ckv) {
    const int k = blockIdx.x * 8 + (threadIdx.x >> 5), lane = threadIdx.x & 31;
    float a[16] = {};
    for (int c = lane; c < 1024; c += 32) {
        const float v = __bfloat162float(ckv[(size_t)k * 1024 + c]);
#pragma unroll
        for (int h = 0; h < 16; h++) a[h] += v * f_qa[h * 1024 + c];
    }
#pragma unroll
    for (int h = 0; h < 16; h++) {
        for (int o = 16; o; o >>= 1) a[h] += __shfl_xor_sync(~0u, a[h], o);
        if (lane == 0) f_s[h * 8192 + k] = a[h];
    }
}
__global__ void fb_softmax() {
    __shared__ float red[32];
    float* s = f_s + blockIdx.x * 8192;
    float m = -INFINITY;
    for (int i = threadIdx.x; i < 8192; i += blockDim.x) m = fmaxf(m, s[i]);
    for (int o = 16; o; o >>= 1) m = fmaxf(m, __shfl_xor_sync(~0u, m, o));
    if ((threadIdx.x & 31) == 0) red[threadIdx.x >> 5] = m;
    __syncthreads();
    m = red[0];
    for (int i = 1; i < (int)(blockDim.x >> 5); i++) m = fmaxf(m, red[i]);
    __syncthreads();
    float l = 0.f;
    for (int i = threadIdx.x; i < 8192; i += blockDim.x) { const float e = __expf(s[i] - m); s[i] = e; l += e; }
    for (int o = 16; o; o >>= 1) l += __shfl_xor_sync(~0u, l, o);
    if ((threadIdx.x & 31) == 0) red[threadIdx.x >> 5] = l;
    __syncthreads();
    l = 0.f;
    for (int i = 0; i < (int)(blockDim.x >> 5); i++) l += red[i];
    const float inv = 1.f / l;
    for (int i = threadIdx.x; i < 8192; i += blockDim.x) s[i] *= inv;
}
__global__ void fb_pv(const __nv_bfloat16* ckv) {
    const int c = blockIdx.y * 256 + threadIdx.x, kb = blockIdx.x * 128;
    float a[16] = {};
    for (int k = kb; k < kb + 128; k++) {
        const float v = __bfloat162float(ckv[(size_t)k * 1024 + c]);
#pragma unroll
        for (int h = 0; h < 16; h++) a[h] += v * f_s[h * 8192 + k];
    }
#pragma unroll
    for (int h = 0; h < 16; h++) f_cc[(blockIdx.x * 16 + h) * 1024 + c] = a[h];
}
__global__ void fb_ctx(const __nv_bfloat16* wuv) {
    __shared__ float cc[1024];
    const int h = blockIdx.x;
    for (int c = threadIdx.x; c < 1024; c += 256) {
        float a = 0.f;
        for (int i = 0; i < 64; i++) a += f_cc[(i * 16 + h) * 1024 + c];
        cc[c] = a;
    }
    __syncthreads();
    float a = 0.f;
    for (int c = 0; c < 1024; c++) a += cc[c] * __bfloat162float(wuv[(size_t)c * 4096 + h * 256 + threadIdx.x]);
    f_ctx[h * 256 + threadIdx.x] = bf16r(a);
}
__global__ void fb_o(const __nv_bfloat16* x, const __nv_bfloat16* wo) {
    __shared__ float red[8][32];
    const int m = blockIdx.x * 32 + (threadIdx.x & 31), p = threadIdx.x >> 5;
    float a = 0.f;
    for (int i = p * 512; i < p * 512 + 512; i++) a += f_ctx[i] * __bfloat162float(wo[(size_t)i * 448 + m]);
    red[p][threadIdx.x & 31] = a;
    __syncthreads();
    if (p == 0) {
        for (int i = 1; i < 8; i++) a += red[i][threadIdx.x];
        f_h[m] = bf16r(__bfloat162float(x[m]) + bf16r(a));
    }
}
__global__ void fb_gu(const __nv_bfloat16* wg, const __nv_bfloat16* wu) {
    __shared__ float hs[448], hn[448];
    for (int i = threadIdx.x; i < 448; i += blockDim.x) hs[i] = f_h[i];
    __syncthreads();
    block_ln(hs, hn);
    const int f = blockIdx.x * 64 + threadIdx.x;
    float a = 0.f, b = 0.f;
    for (int m = 0; m < 448; m++) {
        a += hn[m] * __bfloat162float(wg[(size_t)m * 1792 + f]);
        b += hn[m] * __bfloat162float(wu[(size_t)m * 1792 + f]);
    }
    f_hh[f] = bf16r(bf16r(1.f / (1.f + __expf(-bf16r(a)))) * bf16r(b));
}
__global__ void fb_down(const __nv_bfloat16* wd, __nv_bfloat16* out) {
    __shared__ float red[8][32];
    const int m = blockIdx.x * 32 + (threadIdx.x & 31), p = threadIdx.x >> 5;
    float a = 0.f;
    for (int i = p * 224; i < p * 224 + 224; i++) a += f_hh[i] * __bfloat162float(wd[(size_t)i * 448 + m]);
    red[p][threadIdx.x & 31] = a;
    __syncthreads();
    if (p == 0) {
        for (int i = 1; i < 8; i++) a += red[i][threadIdx.x];
        out[m] = __float2bfloat16_rn(f_h[m] + bf16r(a));
    }
}

typedef CUresult (*EncodeFn)(CUtensorMap*, CUtensorMapDataType, cuuint32_t, void*, const cuuint64_t*, const cuuint64_t*,
                             const cuuint32_t*, const cuuint32_t*, CUtensorMapInterleave, CUtensorMapSwizzle,
                             CUtensorMapL2promotion, CUtensorMapFloatOOBfill);

bool encode3(EncodeFn enc, CUtensorMap* m, const void* p, uint64_t rows, uint64_t rowbytes) {
    cuuint64_t dim[3] = {64, rows, rowbytes / 128};
    cuuint64_t str[2] = {rowbytes, 128};
    cuuint32_t box[3] = {64, 16, 4}, es[3] = {1, 1, 1};
    return enc(m, CU_TENSOR_MAP_DATA_TYPE_BFLOAT16, 3, const_cast<void*>(p), dim, str, box, es, CU_TENSOR_MAP_INTERLEAVE_NONE,
               CU_TENSOR_MAP_SWIZZLE_128B, CU_TENSOR_MAP_L2_PROMOTION_NONE, CU_TENSOR_MAP_FLOAT_OOB_FILL_NONE) == CUDA_SUCCESS;
}
bool encode2(EncodeFn enc, CUtensorMap* m, const void* p, uint64_t rows, uint64_t cols, uint32_t boxrows) {
    cuuint64_t dim[2] = {cols, rows};
    cuuint64_t str[1] = {cols * 2};
    cuuint32_t box[2] = {64, boxrows}, es[2] = {1, 1};
    return enc(m, CU_TENSOR_MAP_DATA_TYPE_BFLOAT16, 2, const_cast<void*>(p), dim, str, box, es, CU_TENSOR_MAP_INTERLEAVE_NONE,
               CU_TENSOR_MAP_SWIZZLE_128B, CU_TENSOR_MAP_L2_PROMOTION_NONE, CU_TENSOR_MAP_FLOAT_OOB_FILL_NONE) == CUDA_SUCCESS;
}

int g_force_fallback = 0;
int g_force_nc = 0;
int g_window = 0x2233;
unsigned g_dly = (24u << 10) | (8u << 15);

}

extern "C" void kernel_launch(void* const* d_in, const int* in_sizes, int n_in, void* d_out, int out_size) {
    const __nv_bfloat16* x = (const __nv_bfloat16*)d_in[0];
    const __nv_bfloat16* ckv = (const __nv_bfloat16*)d_in[1];
    const __nv_bfloat16* wq = (const __nv_bfloat16*)d_in[2];
    const __nv_bfloat16* wuk = (const __nv_bfloat16*)d_in[3];
    const __nv_bfloat16* wuv = (const __nv_bfloat16*)d_in[4];
    const __nv_bfloat16* wo = (const __nv_bfloat16*)d_in[5];
    const __nv_bfloat16* wg = (const __nv_bfloat16*)d_in[7];
    const __nv_bfloat16* wu = (const __nv_bfloat16*)d_in[8];
    const __nv_bfloat16* wd = (const __nv_bfloat16*)d_in[9];
    __nv_bfloat16* out = (__nv_bfloat16*)d_out;
    cudaStream_t st = cudaStreamPerThread;

    static int s_init = 0, s_nc = 0;
    static EncodeFn s_enc = nullptr;
    cudaLaunchConfig_t cfg = {};
    cudaLaunchAttribute at[1];
    at[0].id = cudaLaunchAttributeClusterDimension;
    at[0].val.clusterDim.x = 4; at[0].val.clusterDim.y = 1; at[0].val.clusterDim.z = 1;
    cfg.blockDim = dim3(NTHR); cfg.dynamicSmemBytes = SMEM_BYTES + 128; cfg.stream = st; cfg.attrs = at; cfg.numAttrs = 1;
    if (!s_init) {
        s_init = 1;
        void* fn = nullptr;
        cudaDriverEntryPointQueryResult qr;
        if (cudaGetDriverEntryPoint("cuTensorMapEncodeTiled", &fn, cudaEnableDefault, &qr) == cudaSuccess &&
            qr == cudaDriverEntryPointSuccess)
            s_enc = (EncodeFn)fn;
        int nc = 0;
        cfg.gridDim = dim3(4 * NC_MAX);
        if (cudaFuncSetAttribute(fused_kernel, cudaFuncAttributeMaxDynamicSharedMemorySize, SMEM_BYTES + 128) == cudaSuccess &&
            cudaOccupancyMaxActiveClusters(&nc, fused_kernel, &cfg) == cudaSuccess)
            s_nc = nc > NC_MAX ? NC_MAX : nc;
        (void)cudaGetLastError();
    }
    if (g_force_nc && g_force_nc < s_nc) s_nc = g_force_nc;
    Params P;
    bool ok = s_enc != nullptr && s_nc >= NC_MIN && !g_force_fallback;
    ok = ok && encode3(s_enc, &P.wq, wq, 448, 8192) && encode3(s_enc, &P.wuk, wuk, 1024, 8192) &&
         encode3(s_enc, &P.ckv, ckv, 8192, 2048) && encode3(s_enc, &P.wuv, wuv, 1024, 8192) &&
         encode2(s_enc, &P.wo, wo, 4096, 448, 64) && encode2(s_enc, &P.wg, wg, 448, 1792, 112) &&
         encode2(s_enc, &P.wu, wu, 448, 1792, 112) && encode2(s_enc, &P.wd, wd, 1792, 448, 64);
    if (ok) {
        P.x = x; P.out = out; P.NC = s_nc; P.W = g_window; P.dly = g_dly;
        const int N = 4 * s_nc;
        int ustart[4 * NC_MAX + 1], kstart[NC_MAX + 1];
        {
            const int kbase = 512 / s_nc, kext = 512 - kbase * s_nc;
            kstart[0] = 0;
            for (int jj = 0; jj < s_nc; jj++) kstart[jj + 1] = kstart[jj] + kbase + (jj >= s_nc - kext ? 1 : 0);
            int cap = 0;
            for (int c = 0; c < N; c++) cap += (kstart[(c >> 2) + 1] - kstart[c >> 2] > 17) ? 8 : 9;
            const bool deep = cap >= 1024;
            P.RS = deep ? 5 : 3;
            int nine = 0;
            for (int c = 0; c < N; c++) nine += (!deep || kstart[(c >> 2) + 1] - kstart[c >> 2] <= 17) ? 1 : 0;
            const int uext = 1024 - 8 * N;
            ustart[0] = 0;
            for (int c = 0, i = 0; c < N; c++) {
                int extra = 0;
                if (!deep || kstart[(c >> 2) + 1] - kstart[c >> 2] <= 17) { extra = (i + 1) * uext / nine - i * uext / nine; i++; }
                ustart[c + 1] = ustart[c] + 8 + extra;
            }
        }
        auto owner = [&](int u) { int c = 0; while (ustart[c + 1] <= u) c++; return c; };
        for (int c = 0; c < 4 * NC_MAX; c++) {
            if (c >= N) { P.tab[c] = make_uint2(0, 0); continue; }
            const int jj = c >> 2, u0 = ustart[c], nu = ustart[c + 1] - u0;
            const int k0 = kstart[jj], nk = kstart[jj + 1] - k0;
            const int h7 = (c / 7) & 15, mb7 = c % 7, hA = u0 >> 6, hB = (u0 + nu - 1) >> 6;
            const int ns = owner(h7 * 64 + 63) - owner(h7 * 64) + 1;
            P.tab[c].x = u0 | (nu << 10) | (k0 << 14) | (nk << 23);
            P.tab[c].y = h7 | (mb7 << 4) | ((c - owner(hA * 64)) << 8) | ((c - owner(hB * 64)) << 12) | (ns << 16);
        }
        cfg.gridDim = dim3(4 * s_nc);
        cudaLaunchKernelEx(&cfg, fused_kernel, P);
        return;
    }
    fb_q<<<16, 256, 0, st>>>(x, wq);
    fb_qabs<<<2048, 256, 0, st>>>(wuk);
    fb_scores<<<1024, 256, 0, st>>>(ckv);
    fb_softmax<<<16, 1024, 0, st>>>();
    fb_pv<<<dim3(64, 4), 256, 0, st>>>(ckv);
    fb_ctx<<<16, 256, 0, st>>>(wuv);
    fb_o<<<14, 256, 0, st>>>(x, wo);
    fb_gu<<<28, 64, 0, st>>>(wg, wu);
    fb_down<<<14, 256, 0, st>>>(wd, out);
}
```

```cpp
#include <cuda_runtime.h>
#include <cuda_bf16.h>
#include <cuda.h>
#include <stdint.h>
#include <limits.h>

namespace {

constexpr int NC_MAX = 32, NC_MIN = 29;
constexpr int NTHR = 512;

constexpr uint32_t UNIT = 8192;
constexpr uint32_t OFF_CKV = 0;
constexpr uint32_t OFF_WA = 18 * UNIT;
constexpr uint32_t OFF_X = OFF_WA + 9 * UNIT;
constexpr uint32_t OFF_SLOT = OFF_X;
constexpr uint32_t OFF_PBUF = OFF_X + 3 * 2048;
constexpr uint32_t PSTRIDE = 1088;
constexpr uint32_t OFF_BAR = OFF_PBUF + 4 * PSTRIDE;
constexpr uint32_t OFF_MISC = OFF_BAR + 42 * 8;
constexpr uint32_t OFF_WGT = OFF_CKV + 10 * UNIT;
constexpr uint32_t OFF_REF = OFF_MISC + 16;
constexpr uint32_t OFF_PVC = OFF_REF + 48;
constexpr uint32_t SMEM_BYTES = OFF_PVC + 64;
constexpr uint32_t OFF_QST = OFF_PBUF;
constexpr uint32_t OFF_TILE = OFF_X;
constexpr uint32_t OFF_CTX = OFF_X + 9216;
constexpr uint32_t OFF_AFR = OFF_X + 9728;
constexpr uint32_t OFF_H = OFF_X;
constexpr uint32_t OFF_GU = OFF_X + 1024;
static_assert(OFF_AFR + 576 <= OFF_BAR, "staging overflow");
static_assert(SMEM_BYTES + 128 <= 232448, "smem overflow");

enum { B_S0 = 26, B_P0 = 31, B_H = 37, B_GU = 38, G_P1 = 39, G_QA = 40, NBARS = 41 };

struct __align__(64) Params {
    CUtensorMap wq, wuk, ckv, wuv, wo, wg, wu, wd;
    const __nv_bfloat16* x;
    __nv_bfloat16* out;
    int NC;
    int W;
    unsigned dly;
    int RS;
    uint2 tab[4 * NC_MAX];
};

constexpr uint32_t MB1 = 0;
constexpr uint32_t MB2 = MB1 + 112 * 1024;
constexpr uint32_t MB3 = MB2 + 32768;
constexpr uint32_t MBM = MB3 + 1024 * 1024;
constexpr uint32_t MB4 = MBM + 16384;
constexpr uint32_t MB5 = MB4 + 16 * 12 * 1024;
constexpr uint32_t MB6 = MB5 + 16 * 1792;
constexpr uint32_t MB_SET = (MB6 + 4 * 28 * 28 * 32 + 1023) / 1024 * 1024;
__device__ __align__(1024) unsigned char g_mb[2 * MB_SET];
__device__ unsigned g_epoch;
#define TRACE(i) do {} while (0)

constexpr int SPIN_LIMIT = 1 << 18;
__device__ __forceinline__ void mbar_init(uint32_t b, uint32_t c) {
    asm volatile("mbarrier.init.shared::cta.b64 [%0], %1;" ::"r"(b), "r"(c) : "memory");
}
__device__ __forceinline__ void mbar_expect(uint32_t b, uint32_t bytes) {
    asm volatile("mbarrier.arrive.expect_tx.shared::cta.b64 _, [%0], %1;" ::"r"(b), "r"(bytes) : "memory");
}
__device__ __forceinline__ void mbar_arrive(uint32_t b) {
    asm volatile("mbarrier.arrive.shared::cta.b64 _, [%0];" ::"r"(b) : "memory");
}
__device__ __forceinline__ bool mbar_try(uint32_t b, uint32_t ph) {
    uint32_t ok;
    asm volatile("{.reg .pred p; mbarrier.try_wait.parity.shared::cta.b64 p, [%1], %2; selp.u32 %0,1,0,p;}"
                 : "=r"(ok) : "r"(b), "r"(ph) : "memory");
    return ok;
}
__device__ __forceinline__ bool mbar_test(uint32_t b, uint32_t ph) {
    uint32_t ok;
    asm volatile("{.reg .pred p; mbarrier.test_wait.parity.shared::cta.b64 p, [%1], %2; selp.u32 %0,1,0,p;}"
                 : "=r"(ok) : "r"(b), "r"(ph) : "memory");
    return ok;
}
__device__ __forceinline__ void mbar_wait(uint32_t b, uint32_t ph) {
#pragma unroll 1
    for (int i = 0; i < SPIN_LIMIT; i++)
        if (mbar_try(b, ph)) return;
}
__device__ __forceinline__ void mbar_wait_cl(uint32_t b, uint32_t ph) {
#pragma unroll 1
    for (int i = 0; i < SPIN_LIMIT; i++) {
        uint32_t ok;
        asm volatile("{.reg .pred p; mbarrier.try_wait.parity.acquire.cluster.shared::cta.b64 p, [%1], %2; selp.u32 %0,1,0,p;}"
                     : "=r"(ok) : "r"(b), "r"(ph) : "memory");
        if (ok) return;
    }
}
__device__ __forceinline__ void tma2p(uint32_t dst, const CUtensorMap* m, int x, int y, uint32_t bar, unsigned long long pol) {
    asm volatile("cp.async.bulk.tensor.2d.shared::cluster.global.mbarrier::complete_tx::bytes.L2::cache_hint [%0], [%1, {%3, %4}], [%2], %5;"
                 ::"r"(dst), "l"(m), "r"(bar), "r"(x), "r"(y), "l"(pol) : "memory");
}
__device__ __forceinline__ void tma3p(uint32_t dst, const CUtensorMap* m, int x, int y, int z, uint32_t bar, unsigned long long pol) {
    asm volatile("cp.async.bulk.tensor.3d.shared::cluster.global.mbarrier::complete_tx::bytes.L2::cache_hint [%0], [%1, {%3, %4, %5}], [%2], %6;"
                 ::"r"(dst), "l"(m), "r"(bar), "r"(x), "r"(y), "r"(z), "l"(pol) : "memory");
}
__device__ __forceinline__ uint32_t mapa(uint32_t a, uint32_t rank) {
    uint32_t r;
    asm("mapa.shared::cluster.u32 %0, %1, %2;" : "=r"(r) : "r"(a), "r"(rank));
    return r;
}
__device__ __forceinline__ void st_async_v4(uint32_t a, uint32_t x, uint32_t y, uint32_t z, uint32_t w, uint32_t bar) {
    asm volatile("st.async.weak.shared::cluster.mbarrier::complete_tx::bytes.v4.b32 [%0], {%1,%2,%3,%4}, [%5];"
                 ::"r"(a), "r"(x), "r"(y), "r"(z), "r"(w), "r"(bar) : "memory");
}
__device__ __forceinline__ void st_async_b32(uint32_t a, uint32_t x, uint32_t bar) {
    asm volatile("st.async.weak.shared::cluster.mbarrier::complete_tx::bytes.b32 [%0], %1, [%2];"
                 ::"r"(a), "r"(x), "r"(bar) : "memory");
}
__device__ __forceinline__ void ldsm4(uint32_t a, uint32_t& r0, uint32_t& r1, uint32_t& r2, uint32_t& r3) {
    asm volatile("ldmatrix.sync.aligned.m8n8.x4.shared.b16 {%0,%1,%2,%3}, [%4];"
                 : "=r"(r0), "=r"(r1), "=r"(r2), "=r"(r3) : "r"(a) : "memory");
}
__device__ __forceinline__ void ldsm4t(uint32_t a, uint32_t& r0, uint32_t& r1, uint32_t& r2, uint32_t& r3) {
    asm volatile("ldmatrix.sync.aligned.m8n8.x4.trans.shared.b16 {%0,%1,%2,%3}, [%4];"
                 : "=r"(r0), "=r"(r1), "=r"(r2), "=r"(r3) : "r"(a) : "memory");
}
__device__ __forceinline__ void mma16816(float (&c)[4], uint32_t a0, uint32_t a1, uint32_t a2, uint32_t a3, uint32_t b0, uint32_t b1) {
    asm("mma.sync.aligned.m16n8k16.row.col.f32.bf16.bf16.f32 {%0,%1,%2,%3}, {%4,%5,%6,%7}, {%8,%9}, {%0,%1,%2,%3};"
                 : "+f"(c[0]), "+f"(c[1]), "+f"(c[2]), "+f"(c[3]) : "r"(a0), "r"(a1), "r"(a2), "r"(a3), "r"(b0), "r"(b1));
}
__device__ __forceinline__ uint4 lds128(uint32_t a) {
    uint4 v;
    asm volatile("ld.shared.v4.u32 {%0,%1,%2,%3}, [%4];" : "=r"(v.x), "=r"(v.y), "=r"(v.z), "=r"(v.w) : "r"(a) : "memory");
    return v;
}
__device__ __forceinline__ uint32_t lds32(uint32_t a) {
    uint32_t v;
    asm volatile("ld.shared.u32 %0, [%1];" : "=r"(v) : "r"(a) : "memory");
    return v;
}
__device__ __forceinline__ uint32_t lds32_acq(uint32_t a) {
    uint32_t v;
    asm volatile("ld.acquire.cta.shared.u32 %0, [%1];" : "=r"(v) : "r"(a) : "memory");
    return v;
}
__device__ __forceinline__ uint4 lds128_vol(uint32_t a) {
    uint4 v;
    asm volatile("ld.volatile.shared.v4.u32 {%0,%1,%2,%3}, [%4];" : "=r"(v.x), "=r"(v.y), "=r"(v.z), "=r"(v.w) : "r"(a) : "memory");
    return v;
}
__device__ __forceinline__ void sts128_vol(uint32_t a, uint4 v) {
    asm volatile("st.volatile.shared.v4.u32 [%0], {%1,%2,%3,%4};" ::"r"(a), "r"(v.x), "r"(v.y), "r"(v.z), "r"(v.w) : "memory");
}
__device__ __forceinline__ void red_add_rel(uint32_t a, uint32_t v) {
    asm volatile("red.release.cta.shared.add.u32 [%0], %1;" ::"r"(a), "r"(v) : "memory");
}
__device__ __forceinline__ void pv_wait(uint32_t pvc, int k) {
#pragma unroll 1
    for (int it = 0; it < SPIN_LIMIT * 8; it++)
        if ((int)lds32_acq(pvc + k * 4) >= 8) return;
}
__device__ __forceinline__ void sts128(uint32_t a, uint4 v) {
    asm volatile("st.shared.v4.u32 [%0], {%1,%2,%3,%4};" ::"r"(a), "r"(v.x), "r"(v.y), "r"(v.z), "r"(v.w) : "memory");
}
__device__ __forceinline__ void sts32(uint32_t a, uint32_t v) {
    asm volatile("st.shared.u32 [%0], %1;" ::"r"(a), "r"(v) : "memory");
}
__device__ __forceinline__ void sts16(uint32_t a, uint16_t v) {
    asm volatile("st.shared.u16 [%0], %1;" ::"r"(a), "h"(v) : "memory");
}
__device__ __forceinline__ void bar_sync(int id, int n) {
    asm volatile("bar.sync %0, %1;" ::"r"(id), "r"(n) : "memory");
}
__device__ __forceinline__ float bf16r(float v) { return __bfloat162float(__float2bfloat16_rn(v)); }
__device__ __forceinline__ uint32_t pack2(float lo, float hi) {
    __nv_bfloat162 t = __floats2bfloat162_rn(lo, hi);
    return *reinterpret_cast<uint32_t*>(&t);
}
__device__ __forceinline__ float bflo(uint32_t w) { return __uint_as_float(w << 16); }
__device__ __forceinline__ float bfhi(uint32_t w) { return __uint_as_float(w & 0xffff0000u); }
__device__ __forceinline__ float ex2(float x) {
    float y;
    asm("ex2.approx.ftz.f32 %0, %1;" : "=f"(y) : "f"(x));
    return y;
}
__device__ __forceinline__ uint32_t ldg_early(const uint32_t* p) {
    uint32_t v;
    asm volatile("ld.global.nc.u32 %0, [%1];" : "=r"(v) : "l"(p));
    return v;
}

__device__ __forceinline__ void mb_st2(unsigned char* p, uint32_t a, uint32_t b) {
    asm volatile("{.reg .b64 t; mov.b64 t, {%1,%2}; st.relaxed.gpu.global.b64 [%0], t;}" ::"l"(p), "r"(a), "r"(b) : "memory");
}
__device__ __forceinline__ void mb_put2(unsigned char* p, uint32_t a, uint32_t b) { mb_st2(p, a == 0u ? 0x80000000u : a, b); }
__device__ __forceinline__ void mb_put2f(unsigned char* p, float a, float b) { mb_put2(p, __float_as_uint(a), __float_as_uint(b)); }
__device__ __forceinline__ void mb_clear2(uint32_t off) {
    mb_st2(g_mb + off, 0u, 0u);
    mb_st2(g_mb + MB_SET + off, 0u, 0u);
}
__device__ __forceinline__ uint4 mb_ld4(const unsigned char* p) {
    uint4 v;
    asm volatile("{.reg .b64 a, b; ld.relaxed.gpu.global.v2.b64 {a, b}, [%4]; mov.b64 {%0,%1}, a; mov.b64 {%2,%3}, b;}"
                 : "=r"(v.x), "=r"(v.y), "=r"(v.z), "=r"(v.w) : "l"(p) : "memory");
    return v;
}
template <int N, int STRIDE>
__device__ __forceinline__ void mb_poll(const unsigned char* p, int n, uint4 (&v)[N]) {
#pragma unroll
    for (int i = 0; i < N; i++) v[i] = i < n ? mb_ld4(p + i * STRIDE) : make_uint4(0, 0, 0, 0);
#pragma unroll 1
    for (int it = 0; it < SPIN_LIMIT; it++) {
        uint32_t m = 0xffffffffu;
#pragma unroll
        for (int i = 0; i < N; i++)
            if (i < n) m = min(m, min(v[i].x, v[i].z));
        if (m != 0u) break;
#pragma unroll
        for (int i = 0; i < N; i++)
            if (i < n && (N > 4 || min(v[i].x, v[i].z) == 0u)) v[i] = mb_ld4(p + i * STRIDE);
    }
}
__device__ __forceinline__ void delay(uint32_t clks) {
    const uint32_t t0 = clock();
    while (clock() - t0 < clks) {}
}

template <int N, int STRIDE>
__device__ __forceinline__ void mb_first(const unsigned char* p, int n, uint4 (&v)[N]) {
#pragma unroll
    for (int i = 0; i < N; i++) v[i] = i < n ? mb_ld4(p + i * STRIDE) : make_uint4(0, 0, 0, 0);
}
__device__ __forceinline__ void ln_stats(const float (&v)[14], float& mb, float& den) {
    float s = 0.f;
#pragma unroll
    for (int i = 0; i < 14; i++) s += v[i];
#pragma unroll
    for (int o = 16; o; o >>= 1) s += __shfl_xor_sync(~0u, s, o);
    const float mean = s * (1.f / 448.f);
    float q = 0.f;
#pragma unroll
    for (int i = 0; i < 14; i++) { const float d = v[i] - mean; q += d * d; }
#pragma unroll
    for (int o = 16; o; o >>= 1) q += __shfl_xor_sync(~0u, q, o);
    mb = bf16r(mean);
    den = bf16r(__fsqrt_rn(bf16r(bf16r(q * (1.f / 448.f)) + 1e-5f)));
}
__device__ __forceinline__ void ln_stats1(const float (&v)[14], float c, float& mb, float& den) {
    float s0 = 0.f, s1 = 0.f, q0 = 0.f, q1 = 0.f;
#pragma unroll
    for (int i = 0; i < 7; i++) {
        const float d0 = v[2 * i] - c, d1 = v[2 * i + 1] - c;
        s0 += d0; s1 += d1; q0 += d0 * d0; q1 += d1 * d1;
    }
    float s = s0 + s1, q = q0 + q1;
#pragma unroll
    for (int o = 16; o; o >>= 1) { s += __shfl_xor_sync(~0u, s, o); q += __shfl_xor_sync(~0u, q, o); }
    const float md = s * (1.f / 448.f);
    mb = bf16r(c + md);
    den = bf16r(__fsqrt_rn(bf16r(bf16r(fmaxf(q * (1.f / 448.f) - md * md, 0.f)) + 1e-5f)));
}
__device__ __forceinline__ float ln_apply(float v, float mb, float den) { return __fdiv_rn(bf16r(v - mb), den); }
__device__ __forceinline__ float ln_apply_r(float v, float mb, float rden) { return bf16r(v - mb) * rden; }

__device__ __forceinline__ uint32_t frag_off(int w) {
    const int s = w >> 3, half = (w >> 2) & 1, t = w & 3;
    return (uint32_t)((((s >> 1) * 4 + t) * 4 + (s & 1) * 2 + half) * 4);
}
__device__ __forceinline__ int f2o(float f) { const int i = __float_as_int(f); return i ^ ((i >> 31) & 0x7fffffff); }
__device__ __forceinline__ float o2f(int i) { return __int_as_float(i ^ ((i >> 31) & 0x7fffffff)); }

__device__ __forceinline__ void combine_unit(uint32_t SB, const unsigned char* src, int n, uint4 (&v)[2], int ul, bool isA, int lane) {
#pragma unroll 1
    for (int it = 0; it < SPIN_LIMIT; it++) {
        uint32_t m = 0xffffffffu;
        if (n > 0) m = min(m, min(v[0].x, v[0].z));
        if (n > 1) m = min(m, min(v[1].x, v[1].z));
        if (m != 0u) break;
        if (n > 0 && min(v[0].x, v[0].z) == 0u) v[0] = mb_ld4(src);
        if (n > 1 && min(v[1].x, v[1].z) == 0u) v[1] = mb_ld4(src + 512);
    }
    const uint32_t tile = SB + OFF_TILE + ul * 1024, wgt = SB + OFF_WGT + (isA ? 0 : 128);
    sts128(tile + lane * 16, v[0]);
    sts128(tile + 512 + lane * 16, v[1]);
    bar_sync(2, 352);
    const int t = lane & 3;
    uint32_t b[8];
    const uint32_t ts = tile + ((lane & 7) + (lane & 8)) * 32 + (lane >> 4) * 16;
    ldsm4t(ts, b[0], b[1], b[2], b[3]);
    ldsm4t(ts + 512, b[4], b[5], b[6], b[7]);
    const uint4 w0 = lds128(wgt + t * 16), w1 = lds128(wgt + 64 + t * 16);
    float c0[4] = {}, c1[4] = {}, c2[4] = {}, c3[4] = {};
    mma16816(c0, w0.x, w0.y, w0.z, w0.w, b[0], b[1]);
    mma16816(c1, w0.x, w0.y, w0.z, w0.w, b[2], b[3]);
    mma16816(c2, w1.x, w1.y, w1.z, w1.w, b[4], b[5]);
    mma16816(c3, w1.x, w1.y, w1.z, w1.w, b[6], b[7]);
    const float v0 = (c0[0] + c0[2]) + (c2[0] + c2[2]), v1 = (c0[1] + c0[3]) + (c2[1] + c2[3]);
    const float v2 = (c1[0] + c1[2]) + (c3[0] + c3[2]), v3 = (c1[1] + c1[3]) + (c3[1] + c3[3]);
    const uint32_t a0 = pack2(v0, v1), a2 = pack2(v2, v3);
    const uint32_t a1 = pack2(v0 - bflo(a0), v1 - bfhi(a0)), a3 = pack2(v2 - bflo(a2), v3 - bfhi(a2));
    if (lane < 4) sts128(SB + OFF_AFR + ul * 64 + t * 16, make_uint4(a0, a1, a2, a3));
}
__device__ __forceinline__ void reset_unit(const unsigned char* src, int n) {
    if (n > 0) asm volatile("st.relaxed.gpu.global.v2.b64 [%0], {%1,%1};" ::"l"(src), "l"(0ull) : "memory");
    if (n > 1) asm volatile("st.relaxed.gpu.global.v2.b64 [%0], {%1,%1};" ::"l"(src + 512), "l"(0ull) : "memory");
}

__device__ __forceinline__ void qabs_unit(uint32_t SB, unsigned char* dst, int ul, bool second_head, uint32_t bar, int lane) {
    const int row = (lane & 7) + (lane & 8), cs = lane >> 4;
    const uint32_t qs = SB + OFF_QST + (second_head ? 512 : 0) + (lane & 3) * 16;
    uint4 q[8];
#pragma unroll
    for (int s2 = 0; s2 < 8; s2++) q[s2] = lds128(qs + s2 * 64);
    mbar_wait(bar, 0);
    float c[4][4] = {};
    const uint32_t a0 = SB + OFF_WA + ul * UNIT + row * 128;
#pragma unroll
    for (int s2 = 0; s2 < 8; s2++) {
        uint32_t r0, r1, r2, r3, r4, r5, r6, r7;
        ldsm4(a0 + (s2 >> 1) * 2048 + ((((s2 & 1) * 4 + cs) ^ (row & 7)) << 4), r0, r1, r2, r3);
        ldsm4(a0 + (s2 >> 1) * 2048 + ((((s2 & 1) * 4 + 2 + cs) ^ (row & 7)) << 4), r4, r5, r6, r7);
        mma16816(c[(s2 & 1) * 2], r0, r1, r2, r3, q[s2].x, q[s2].y);
        mma16816(c[(s2 & 1) * 2 + 1], r4, r5, r6, r7, q[s2].z, q[s2].w);
    }
    const float sc = 0.0625f * 1.4426950408889634f;
    const float lo = ((c[0][0] + c[1][0]) + (c[2][0] + c[3][0])) * sc, hi = ((c[0][2] + c[1][2]) + (c[2][2] + c[3][2])) * sc;
    const float lo2 = __shfl_down_sync(~0u, lo, 4), hi2 = __shfl_down_sync(~0u, hi, 4);
    if ((lane & 7) == 0) mb_put2(dst, pack2(lo, lo2), pack2(hi, hi2));
}

__global__ void __launch_bounds__(NTHR, 1) fused_kernel(const __grid_constant__ Params P) {
    extern __shared__ __align__(1024) unsigned char smem_raw[];
    const uint32_t SB = (uint32_t)__cvta_generic_to_shared(smem_raw);
    const int tid = threadIdx.x, warp = tid >> 5, lane = tid & 31;
    const int g = lane >> 2, t = lane & 3;
    const int cta = blockIdx.x, j = cta >> 2, r = cta & 3;
    const uint2 tab = P.tab[cta];
    const int u0 = tab.x & 1023, nu = (tab.x >> 10) & 15, k0 = (tab.x >> 14) & 511, nk = (tab.x >> 23) & 31;
    const int h7 = tab.y & 15, mb7 = (tab.y >> 4) & 7;
    const bool full = cta < 112;
    const int nb = (nk + 1) >> 1, nbg = nk >> 1;
    const int g_uk = full ? 2 : 0, g_kv = g_uk + 4, g_uv = g_kv + nbg, g_wo = g_uv + 4, g_gu = g_wo + 2, g_wd = g_gu + 2;
    auto BAR = [&](int i) -> uint32_t { return SB + OFF_BAR + 8 * i; };

    if (warp == 11) {
        const int W1 = P.W & 15, W2 = (P.W >> 4) & 15, W3 = (P.W >> 8) & 15, W4 = (P.W >> 12) & 15, ngroups = full ? g_wd + 1 : g_wo;
        int done = 0;
        unsigned long long pol;
        asm volatile("createpolicy.fractional.L2::evict_first.b64 %0, 1.0;" : "=l"(pol));
        if (lane < 8) asm volatile("prefetch.tensormap [%0];" ::"l"(reinterpret_cast<const char*>(&P) + lane * 128) : "memory");
#pragma unroll 1
        for (int gi = 0; gi < ngroups; gi++) {
            if (gi == min(W1, 4)) {
                if (lane == 0) {
                    for (int i = gi; i < 4; i++) mbar_init(BAR(i), 1);
                    asm volatile("fence.mbarrier_init.release.cluster;" ::: "memory");
                }
                __syncthreads();
                asm volatile("barrier.cluster.arrive.relaxed.aligned;" ::: "memory");
            }
            const CUtensorMap* map;
            uint32_t dst, dstep = UNIT;
            int n = 2, x0 = 0, y0, z0 = -1, x1 = 0, y1, z1 = 0, y2 = 0, z2 = 0, gate = -1, pvgate = 0;
            if (gi < g_uk) {
                map = &P.wq; dst = OFF_CKV + (14 + 2 * gi) * UNIT;
                y0 = mb7 * 64 + gi * 32; y1 = y0 + 16; z0 = z1 = h7 * 4;
            } else if (gi < g_kv || (gi >= g_uv && gi < g_wo)) {
                const bool uv = gi >= g_uv;
                const int i0 = 2 * (gi - (uv ? g_uv : g_uk)), u = u0 + i0;
                if (gi == g_uv) gate = G_QA;
                map = uv ? &P.wuv : &P.wuk; dst = OFF_WA + i0 * UNIT; n = i0 == 6 ? nu - 6 : 2;
                y0 = (u & 63) * 16; z0 = (u >> 6) * 4; y1 = ((u + 1) & 63) * 16; z1 = ((u + 1) >> 6) * 4;
                y2 = ((u + 2) & 63) * 16; z2 = ((u + 2) >> 6) * 4;
            } else if (gi < g_uv) {
                const int b = gi - g_kv;
                if (b == 7 && full) gate = G_P1;
                map = &P.ckv; dst = OFF_CKV + 2 * b * UNIT; n = b == nbg - 1 ? nk - 2 * b : 2;
                y0 = (k0 + 2 * b) * 16; y1 = y0 + 16; y2 = y0 + 32; z0 = z1 = z2 = r * 4;
            } else if (gi < g_gu) {
                const int i = gi - g_wo;
                pvgate = 1;
                map = &P.wo; dst = OFF_CKV + 2 * i * UNIT;
                x0 = x1 = mb7 * 64; y0 = h7 * 256 + i * 128; y1 = y0 + 64;
            } else if (gi < g_wd) {
                const int i = gi - g_gu;
                pvgate = 3;
                map = (r & 1) ? &P.wu : &P.wg; dst = OFF_CKV + 4 * UNIT + i * 14336; n = 1; dstep = 14336;
                x0 = j * 64; y0 = (r >> 1) * 224 + i * 112; y1 = 0;
            } else {
                pvgate = 4;
                map = &P.wd; dst = OFF_CKV + 8 * UNIT;
                x0 = r * 112; x1 = x0 + 64; y0 = y1 = j * 64;
            }
            if (gate >= 0) mbar_wait(BAR(gate), 0);
            if (pvgate) pv_wait(SB + OFF_PVC, pvgate);
            {
                const int W = gi < g_kv ? W1 : gi < g_uv ? W2 : gi < g_wo ? W3 : W4;
#pragma unroll 1
                for (; done <= gi - W; done++) mbar_wait(BAR(done), 0);
            }
            if (lane == 0) {
                const uint32_t bar = BAR(gi);
                if (gi < min(W1, 4)) {
                    mbar_init(bar, 1);
                    asm volatile("fence.mbarrier_init.release.cluster;" ::: "memory");
                }
                mbar_expect(bar, n * dstep);
                if (z0 >= 0) {
                    tma3p(SB + dst, map, 0, y0, z0, bar, pol);
                    tma3p(SB + dst + UNIT, map, 0, y1, z1, bar, pol);
                    if (n > 2) tma3p(SB + dst + 2 * UNIT, map, 0, y2, z2, bar, pol);
                } else {
                    tma2p(SB + dst, map, x0, y0, bar, pol);
                    if (n > 1) tma2p(SB + dst + UNIT, map, x1, y1, bar, pol);
                }
                if (gi == g_kv) TRACE(15);
                if (gi == g_uv) TRACE(19);
                if (gi == g_wo) TRACE(20);
            }
            __syncwarp();
        }
        if (lane == 0) TRACE(31);
        asm volatile("barrier.cluster.wait.acquire.aligned;" ::: "memory");
        return;
    }

    uint32_t epoch, xr[7], xa[8], xw0, xw1;
    {
        const uint32_t* x32 = reinterpret_cast<const uint32_t*>(P.x);
        asm volatile("ld.relaxed.gpu.global.u32 %0, [%1];" : "=r"(epoch) : "l"(&g_epoch) : "memory");
#pragma unroll
        for (int i = 0; i < 7; i++) xr[i] = ldg_early(x32 + lane + 32 * i);
#pragma unroll
        for (int i = 0; i < 8; i++) xa[i] = ldg_early(x32 + mb7 * 32 + (i >> 1) * 8 + (i & 1) * 4 + t);
        xw0 = ldg_early(x32 + r * 56 + 2 * min(lane, 27));
        xw1 = ldg_early(x32 + r * 56 + 2 * min(lane, 27) + 1);
    }
    if (lane == 0) {
#pragma unroll 1
        for (int i = 4 + (warp > 11 ? warp - 1 : warp); i < NBARS; i += 15) mbar_init(BAR(i), i == G_P1 ? 8 : i == G_QA ? 4 : i == B_GU ? 2 : 1);
        if (warp >= 8 && warp < 11) sts128(SB + OFF_REF + (warp - 8) * 16, make_uint4(0, 0, 0, 0));
        if (warp >= 12) sts128(SB + OFF_PVC + (warp - 12) * 16, make_uint4(0, 0, 0, 0));
        asm volatile("fence.mbarrier_init.release.cluster;" ::: "memory");
    }
    __syncthreads();
    asm volatile("barrier.cluster.arrive.relaxed.aligned;" ::: "memory");
    const int NC = P.NC;
    const int hA = u0 >> 6, hB = (u0 + nu - 1) >> 6;
    const int RS = P.RS, RP = RS + 1;
    const uint32_t xoff = nk <= 17 ? OFF_CKV + 17 * UNIT : OFF_WA + 8 * UNIT;
    auto slot_off = [&](int i) -> uint32_t { return i < 3 ? OFF_SLOT + i * 2048 : xoff + (i - 3) * 2048; };
    auto p_off = [&](int i) -> uint32_t { return i < 4 ? OFF_PBUF + i * PSTRIDE : xoff + 4096 + (i - 4) * PSTRIDE; };

    if (warp >= 12) {
        const int nt = warp - 12;
        const uint32_t s_dst = mapa(SB + r * 512 + (nt * 2 + (g >> 2)) * 64 + t * 16, g & 3);
        const uint32_t s_bar = mapa(BAR(B_S0), g & 3);
        const int srow = (nt & 1) * 8 + (lane & 7);
        const uint32_t s_src0 = SB + OFF_CKV + (nt >> 1) * UNIT + srow * 128 + (((lane >> 3) ^ (srow & 7)) << 4);
        const uint32_t s_src1 = SB + OFF_CKV + (nt >> 1) * UNIT + srow * 128 + (((4 + (lane >> 3)) ^ (srow & 7)) << 4);
        unsigned char* const mb = g_mb + (epoch & 1) * MB_SET;
        const int ht = tid - 384;
        bar_sync(13, 384);
        delay((P.dly & 31) * 64);
        if (ht < 64 || hB != hA) {
            const int i = ht & 63, hs = ht >> 6;
            uint4 v[7];
            mb_poll<7, 1024>(mb + MB1 + (hs ? hB : hA) * 7168 + i * 16, 7, v);
            float a0 = 0.f, a1 = 0.f, a2 = 0.f, a3 = 0.f;
#pragma unroll
            for (int k = 0; k < 7; k++) {
                a0 += __uint_as_float(v[k].x); a1 += __uint_as_float(v[k].y);
                a2 += __uint_as_float(v[k].z); a3 += __uint_as_float(v[k].w);
            }
            const uint32_t d = SB + OFF_QST + hs * 512 + frag_off(2 * i);
            sts32(d, pack2(a0, a1));
            sts32(d + 16, pack2(a2, a3));
        }
        asm volatile("bar.arrive 7, 416;" ::: "memory");
        asm volatile("barrier.cluster.wait.acquire.aligned;" ::: "memory");
        {
            bar_sync(6, 416);
            delay(((P.dly >> 5) & 31) * 64);
            uint4 v[4];
            mb_poll<4, 2048>(mb + MB2 + r * 8192 + ht * 16, 4, v);
            const uint32_t a = SB + OFF_WA + ((ht >> 1) & 15) * 512 + ((ht >> 5) * 4 + (ht & 1) * 2) * 16;
            sts128(a, make_uint4(v[0].x, v[2].x, v[0].y, v[2].y));
            sts128(a + 16, make_uint4(v[0].z, v[2].z, v[0].w, v[2].w));
            sts128(a + 256, make_uint4(v[1].x, v[3].x, v[1].y, v[3].y));
            sts128(a + 272, make_uint4(v[1].z, v[3].z, v[1].w, v[3].w));
            bar_sync(9, 128);
        }
        if (ht == 0) TRACE(4);
        uint32_t qa[16][4];
#pragma unroll
        for (int s = 0; s < 16; s++) {
            const uint4 q = lds128(SB + OFF_WA + s * 512 + lane * 16);
            qa[s][0] = q.x; qa[s][1] = q.y; qa[s][2] = q.z; qa[s][3] = q.w;
        }
        __syncwarp();
        if (lane == 0) mbar_arrive(BAR(G_QA));
        const int nbs = (nk - (nt >> 1) + 1) >> 1;
        int sb = 0;
        bool landed = false;
#pragma unroll 1
        for (int b = 0; b < nbs; b++) {
            if (!landed) mbar_wait(BAR(g_kv + b), 0);
            float c0[4] = {}, c1[4] = {}, c2[4] = {}, c3[4] = {};
#pragma unroll
            for (int i = 0; i < 4; i++) {
                uint32_t b0, b1, b2, b3, b4, b5, b6, b7;
                ldsm4(s_src0 + 2 * b * UNIT + i * 2048, b0, b1, b2, b3);
                ldsm4(s_src1 + 2 * b * UNIT + i * 2048, b4, b5, b6, b7);
                mma16816(c0, qa[4 * i][0], qa[4 * i][1], qa[4 * i][2], qa[4 * i][3], b0, b1);
                mma16816(c1, qa[4 * i + 1][0], qa[4 * i + 1][1], qa[4 * i + 1][2], qa[4 * i + 1][3], b2, b3);
                mma16816(c2, qa[4 * i + 2][0], qa[4 * i + 2][1], qa[4 * i + 2][2], qa[4 * i + 2][3], b4, b5);
                mma16816(c3, qa[4 * i + 3][0], qa[4 * i + 3][1], qa[4 * i + 3][2], qa[4 * i + 3][3], b6, b7);
            }
            landed = b + 1 >= nbg || mbar_test(BAR(g_kv + b + 1), 0);
            if (b >= RS) pv_wait(SB + OFF_PVC, b - RS);
            st_async_v4(s_dst + slot_off(sb), __float_as_uint((c0[0] + c1[0]) + (c2[0] + c3[0])),
                        __float_as_uint((c0[1] + c1[1]) + (c2[1] + c3[1])), __float_as_uint((c0[2] + c1[2]) + (c2[2] + c3[2])),
                        __float_as_uint((c0[3] + c1[3]) + (c2[3] + c3[3])), s_bar + sb * 8);
            if (++sb == RS) sb = 0;
        }
        if (!full) return;
        if (nt < 2) {
            bar_sync(10, 320);
            delay(((P.dly >> 15) & 31) * 64);
            uint4 v[10];
            mb_poll<10, 1024>(mb + MB4 + h7 * 12288 + ht * 16, (tab.y >> 16) & 15, v);
            float a0 = 0.f, a1 = 0.f, a2 = 0.f, a3 = 0.f, e0 = 0.f, e1 = 0.f, e2 = 0.f, e3 = 0.f;
#pragma unroll
            for (int k = 0; k < 5; k++) {
                a0 += __uint_as_float(v[k].x); a1 += __uint_as_float(v[k].y);
                a2 += __uint_as_float(v[k].z); a3 += __uint_as_float(v[k].w);
                e0 += __uint_as_float(v[5 + k].x); e1 += __uint_as_float(v[5 + k].y);
                e2 += __uint_as_float(v[5 + k].z); e3 += __uint_as_float(v[5 + k].w);
            }
            bar_sync(4, 96);
            const float rl = __uint_as_float(lds32(SB + OFF_MISC));
            const uint32_t d = SB + OFF_CTX + frag_off(2 * ht);
            sts32(d, pack2((a0 + e0) * rl, (a1 + e1) * rl));
            sts32(d + 16, pack2((a2 + e2) * rl, (a3 + e3) * rl));
            asm volatile("bar.arrive 8, 320;" ::: "memory");
        } else if (nt == 2) {
            bar_sync(11, 288);
            delay(((P.dly >> 20) & 31) * 64);
            if (lane < 28) {
                const int w = (r & 1) * 56 + 2 * lane;
                const uint32_t d0 = SB + OFF_H + (r >> 1) * 448 + frag_off(w);
                uint32_t da[4], ba[4];
#pragma unroll
                for (int k = 0; k < 4; k++) { da[k] = mapa(d0, k); ba[k] = mapa(BAR(B_H), k); }
                uint4 v[16];
                mb_poll<16, 1792>(mb + MB5 + r * 448 + lane * 16, 16, v);
                float a[4][4] = {};
#pragma unroll
                for (int k = 0; k < 16; k++) {
                    a[k & 3][0] += __uint_as_float(v[k].x); a[k & 3][1] += __uint_as_float(v[k].y);
                    a[k & 3][2] += __uint_as_float(v[k].z); a[k & 3][3] += __uint_as_float(v[k].w);
                }
                const uint32_t h0 = pack2(bflo(xw0) + bf16r((a[0][0] + a[1][0]) + (a[2][0] + a[3][0])),
                                          bfhi(xw0) + bf16r((a[0][1] + a[1][1]) + (a[2][1] + a[3][1])));
                const uint32_t h1 = pack2(bflo(xw1) + bf16r((a[0][2] + a[1][2]) + (a[2][2] + a[3][2])),
                                          bfhi(xw1) + bf16r((a[0][3] + a[1][3]) + (a[2][3] + a[3][3])));
#pragma unroll
                for (int k = 0; k < 4; k++) {
                    st_async_b32(da[k], h0, ba[k]);
                    st_async_b32(da[k] + 16, h1, ba[k]);
                }
            }
        } else {
            const int k = (lane >> 1) & 3;
            mbar_wait_cl(BAR(B_H), 0);
            {
                float v[14], mean, den;
#pragma unroll
                for (int i = 0; i < 7; i++) {
                    const uint32_t w = lds32(SB + OFF_H + (lane + 32 * i) * 4);
                    v[2 * i] = bflo(w); v[2 * i + 1] = bfhi(w);
                }
                ln_stats1(v, bflo(lds32(SB + OFF_H)), mean, den);
                if (lane == 0) {
                    sts32(SB + OFF_MISC + 8, __float_as_uint(mean));
                    sts32(SB + OFF_MISC + 12, __float_as_uint(__fdividef(1.f, den)));
                    mbar_arrive(BAR(B_GU));
                }
            }
            const uint32_t hw = lds32(SB + OFF_H + (r >> 1) * 448 + frag_off((r & 1) * 56 + j * 2 + (k >> 1)));
            uint4 v[4];
            const int n = lane < 4 ? 4 : lane < 8 ? 3 : 0;
            bar_sync(12, 288);
            delay(((P.dly >> 25) & 31) * 64);
            mb_poll<4, 256>(mb + MB6 + ((r * 28 + j) * 28 + lane) * 32, n, v);
            float v0 = (__uint_as_float(v[0].x) + __uint_as_float(v[1].x)) + (__uint_as_float(v[2].x) + __uint_as_float(v[3].x));
            float v1 = (__uint_as_float(v[0].y) + __uint_as_float(v[1].y)) + (__uint_as_float(v[2].y) + __uint_as_float(v[3].y));
            float v2 = (__uint_as_float(v[0].z) + __uint_as_float(v[1].z)) + (__uint_as_float(v[2].z) + __uint_as_float(v[3].z));
            float v3 = (__uint_as_float(v[0].w) + __uint_as_float(v[1].w)) + (__uint_as_float(v[2].w) + __uint_as_float(v[3].w));
            __syncwarp();
            const bool up = lane & 4;
            const float s0 = up ? v0 : v2, s1 = up ? v1 : v3;
            const float k0v = up ? v2 : v0, k1v = up ? v3 : v1;
            v0 = k0v + __shfl_xor_sync(~0u, s0, 4);
            v1 = k1v + __shfl_xor_sync(~0u, s1, 4);
            const bool up2 = lane & 2;
            const float s2 = up2 ? v0 : v1, k2v = up2 ? v1 : v0;
            v0 = k2v + __shfl_xor_sync(~0u, s2, 2);
            v0 += __shfl_xor_sync(~0u, v0, 1);
            if (lane < 8 && (lane & 1) == 0)
                P.out[r * 112 + j * 4 + k] = __float2bfloat16_rn(((k & 1) ? bfhi(hw) : bflo(hw)) + bf16r(v0));
            if (cta == 0 && lane == 0) g_epoch = epoch + 1;
            if (lane == 0) TRACE(13);
        }
        return;
    }
    if (warp >= 8) {
        const int sb = warp - 8, nt = lane >> 3, gg = (lane >> 2) & 1;
        if (lane == 0) {
            mbar_expect(BAR(B_S0 + sb), 2048);
            if (sb + 3 < RS) mbar_expect(BAR(B_S0 + sb + 3), 2048);
        }
        const uint32_t dst_a = mapa(SB + (nt >> 1) * 512 + ((r + 4 * gg) * 4 + t) * 16, (nt & 1) * 2);
        const uint32_t dst_b = mapa(SB + (nt >> 1) * 512 + ((r + 4 * gg) * 4 + t) * 16, (nt & 1) * 2 + 1);
        const uint32_t bar_a = mapa(BAR(B_P0), (nt & 1) * 2), bar_b = mapa(BAR(B_P0), (nt & 1) * 2 + 1);
        const uint32_t dst_m = mapa(SB + 1024 + (r + 4 * gg + 8 * nt) * 4, t), bar_m = mapa(BAR(B_P0), t);
        const uint32_t ref_prev = SB + OFF_REF + (sb == 0 ? 2 : sb - 1) * 16;
        if (sb == 0) {
            const int ub = u0 + 8;
            const uint32_t o2b = MB2 + ((((ub & 63) >> 4) * 16 + (ub >> 6)) * 16 + (ub & 15)) * 32 + (lane >> 3) * 8;
            if (nu > 8 && (lane & 7) == 0) mb_clear2(o2b);
            bar_sync(7, 416);
            if (nu > 8) qabs_unit(SB, g_mb + (epoch & 1) * MB_SET + o2b, 8, (ub >> 6) != hA, BAR(g_uk + 3), lane);
            asm volatile("bar.arrive 6, 416;" ::: "memory");
        }
        asm volatile("barrier.cluster.wait.acquire.aligned;" ::: "memory");
#pragma unroll 1
        for (int b = sb; b < nb; b += 3) {
            const int si = b >= RS ? (b >= 2 * RS ? b - 2 * RS : b - RS) : b, sph = (b >= RS && b < 2 * RS) ? 1 : 0;
            const int pi = b >= RP ? (b >= 2 * RP ? b - 2 * RP : b - RP) : b;
            const uint32_t po = p_off(pi), bo = pi * 8, sa = SB + slot_off(si) + lane * 16;
            const bool valid = 2 * b + (nt >> 1) < nk;
            if (b >= RS) {
                const uint32_t tk = SB + OFF_REF + ((b - RS) % 3) * 16;
#pragma unroll 1
                for (int it = 0; it < SPIN_LIMIT * 8; it++)
                    if ((int)(lds128_vol(tk).x & 15u) > b - RS) break;
            }
            mbar_wait_cl(BAR(B_S0 + si), sph);
            if (lane == 0 && b == 5) TRACE(16);
            const uint4 v0 = lds128(sa), v1 = lds128(sa + 512), v2 = lds128(sa + 1024), v3 = lds128(sa + 1536);
            float s0 = (__uint_as_float(v0.x) + __uint_as_float(v1.x)) + (__uint_as_float(v2.x) + __uint_as_float(v3.x));
            float s1 = (__uint_as_float(v0.y) + __uint_as_float(v1.y)) + (__uint_as_float(v2.y) + __uint_as_float(v3.y));
            float s2 = (__uint_as_float(v0.z) + __uint_as_float(v1.z)) + (__uint_as_float(v2.z) + __uint_as_float(v3.z));
            float s3 = (__uint_as_float(v0.w) + __uint_as_float(v1.w)) + (__uint_as_float(v2.w) + __uint_as_float(v3.w));
            const int i0 = valid ? f2o(fmaxf(s0, s1)) : INT_MIN, i1 = valid ? f2o(fmaxf(s2, s3)) : INT_MIN;
            int ra = __reduce_max_sync(~0u, gg ? INT_MIN : i0), rb = __reduce_max_sync(~0u, gg ? i0 : INT_MIN);
            int rc = __reduce_max_sync(~0u, gg ? INT_MIN : i1), rd = __reduce_max_sync(~0u, gg ? i1 : INT_MIN);
            ra = (ra + 15) & ~15; rb = (rb + 15) & ~15; rc = (rc + 15) & ~15; rd = (rd + 15) & ~15;
            if (b > 0) {
                uint4 pr;
#pragma unroll 1
                for (int it = 0; it < SPIN_LIMIT * 8; it++) {
                    pr = lds128_vol(ref_prev);
                    if ((int)(pr.x & pr.y & pr.z & pr.w & 15u) == b && (int)((pr.x | pr.y | pr.z | pr.w) & 15u) == b) break;
                }
                ra = max(ra, (int)pr.x - b); rb = max(rb, (int)pr.y - b); rc = max(rc, (int)pr.z - b); rd = max(rd, (int)pr.w - b);
            }
            __syncwarp();
            if (lane == 0) sts128_vol(SB + OFF_REF + sb * 16, make_uint4(ra | (b + 1), rb | (b + 1), rc | (b + 1), rd | (b + 1)));
            const float n0 = o2f(gg ? rb : ra), n1 = o2f(gg ? rd : rc);
            const uint32_t w0 = pack2(ex2(s0 - n0), ex2(s1 - n0)), w1 = pack2(ex2(s2 - n1), ex2(s3 - n1));
            const uint32_t o0 = __shfl_xor_sync(~0u, w0, 8), o1 = __shfl_xor_sync(~0u, w1, 8);
            if (lane < 16) st_async_b32(dst_m + po, __float_as_uint(nt ? n1 : n0), bar_m + bo);
            if (valid) {
                const bool odd = nt & 1;
                const uint32_t x0 = odd ? o0 : w0, x1 = odd ? o1 : w1, x2 = odd ? w0 : o0, x3 = odd ? w1 : o1;
                st_async_v4(dst_a + po, x0, x1, x2, x3, bar_a + bo);
                st_async_v4(dst_b + po, x0, x1, x2, x3, bar_b + bo);
            }
            if (lane == 0 && b == 5) TRACE(17);
            if (lane == 0 && b + RS < nb) mbar_expect(BAR(B_S0 + si), (2 * (b + RS) + 1 < nk) ? 2048 : 1024);
        }
        bar_sync(5, 352);
        delay(((P.dly >> 10) & 31) * 64);
        const unsigned char* mbp = g_mb + (epoch & 1) * MB_SET;
        if (sb == 2) {
            const unsigned char* src = g_mb + MB3 + (u0 + 8) * 1024 + lane * 16;
            const int n = nu > 8 ? ((16 + (lane >> 1) < NC) ? 2 : 1) : 0;
            uint4 v[2];
            mb_first<2, 512>(src, n, v);
            combine_unit(SB, src, n, v, 8, 8 < (hA + 1) * 64 - u0, lane);
            asm volatile("bar.arrive 3, 288;" ::: "memory");
            reset_unit(src, n);
        } else {
#pragma unroll 1
            for (int pass = 0; pass < ((sb == 0 && full) ? 2 : 1); pass++) {
                const unsigned char* pm = mbp + MBM + ((pass ? h7 : sb ? hB : hA) * NC_MAX + lane) * 32;
                uint2 a = make_uint2(0xff800000u, 0);
                if (lane < NC) {
#pragma unroll 1
                    for (int it = 0; it < SPIN_LIMIT; it++) {
                        asm volatile("{.reg .b64 t; ld.relaxed.gpu.global.b64 t, [%2]; mov.b64 {%0,%1}, t;}" : "=r"(a.x), "=r"(a.y) : "l"(pm) : "memory");
                        if (a.x != 0u) break;
                    }
                }
                __syncwarp();
                const float mj = __uint_as_float(a.x);
                const float w = ex2(mj - o2f(__reduce_max_sync(~0u, f2o(mj))));
                if (pass == 0) {
                    const int jj = lane & 15;
                    const uint32_t d = SB + OFF_WGT + sb * 128 + ((lane >> 4) * 4 + ((jj & 7) >> 1)) * 16 + (jj >> 3) * 8 + (jj & 1) * 2;
                    const __nv_bfloat16 hi = __float2bfloat16_rn(w), lo = __float2bfloat16_rn(w - __bfloat162float(hi));
                    sts16(d, *reinterpret_cast<const uint16_t*>(&hi));
                    sts16(d + 4, *reinterpret_cast<const uint16_t*>(&lo));
                    asm volatile("bar.arrive 2, 352;" ::: "memory");
                } else {
                    float L = w * __uint_as_float(a.y);
#pragma unroll
                    for (int o = 16; o; o >>= 1) L += __shfl_xor_sync(~0u, L, o);
                    if (lane == 0) sts32(SB + OFF_MISC, __float_as_uint(__fdividef(1.f, L)));
                    asm volatile("bar.arrive 4, 96;" ::: "memory");
                }
            }
        }
        return;
    }

    if (tid == 0) {
#pragma unroll 1
        for (int i = 0; i < RP; i++) mbar_expect(BAR(B_P0 + i), 1088);
        mbar_expect(BAR(B_H), 896);
        mbar_expect(BAR(B_GU), 2048);
    }
    const uint32_t o1 = MB1 + cta * 1024 + warp * 128 + lane * 8;
    const uint32_t o3 = MB3 + ((g * 64 + r * 16 + warp * 2) * NC_MAX + j) * 32 + t * 8;
    const bool a4 = g < 4 || hB != hA;
    const uint32_t o4 = MB4 + ((g < 4 ? hA : hB) * 12 + ((tab.y >> (g < 4 ? 8 : 12)) & 15)) * 1024 + warp * 128 + (lane & 15) * 8;
    const uint32_t o5 = MB5 + h7 * 1792 + mb7 * 256 + warp * 32 + t * 8;
    const int li6 = (warp + 8 * (g & 1)) * 4 + t;
    const bool a6 = g < 4 && ((g & 1) == 0 || warp < 6);
    const uint32_t o6 = MB6 + ((r * 28 + (li6 >> 1)) * 28 + j) * 32 + (g >> 1) * 16 + (li6 & 1) * 8;
    const bool am = tid < 32 && (g & 3) == r;
    const uint32_t om = MBM + (g * NC_MAX + j) * 32 + t * 8;
    const int ua = u0 + warp;
    const uint32_t o2a = MB2 + ((((ua & 63) >> 4) * 16 + (ua >> 6)) * 16 + (ua & 15)) * 32 + (lane >> 3) * 8;
    if (full && lane < 16) mb_clear2(o1);
    if ((lane & 7) == 0) mb_clear2(o2a);
    unsigned char* const mb = g_mb + (epoch & 1) * MB_SET;

    if (full) {
        float v[14];
#pragma unroll
        for (int i = 0; i < 7; i++) { v[2 * i] = bflo(xr[i]); v[2 * i + 1] = bfhi(xr[i]); }
        float mean, den;
        ln_stats(v, mean, den);
        const float rden = __frcp_rn(den);
#pragma unroll
        for (int i = 0; i < 8; i++) xa[i] = pack2(ln_apply_r(bflo(xa[i]), mean, rden), ln_apply_r(bfhi(xa[i]), mean, rden));
        if (tid == 0) TRACE(14);
        float acc[4][4] = {};
        const int row = (lane & 7) + (lane & 8), ch = (warp & 1) * 4 + (lane >> 4);
        const uint32_t a0 = SB + OFF_CKV + 14 * UNIT + (warp >> 1) * 2048 + row * 128;
#pragma unroll
        for (int s = 0; s < 4; s++) {
            if ((s & 1) == 0) mbar_wait(BAR(s >> 1), 0);
            uint32_t b0, b1, b2, b3, b4, b5, b6, b7;
            ldsm4t(a0 + s * UNIT + ((ch ^ (row & 7)) << 4), b0, b1, b2, b3);
            ldsm4t(a0 + s * UNIT + (((ch + 2) ^ (row & 7)) << 4), b4, b5, b6, b7);
            mma16816(acc[0], xa[2 * s], 0, xa[2 * s + 1], 0, b0, b1);
            mma16816(acc[1], xa[2 * s], 0, xa[2 * s + 1], 0, b2, b3);
            mma16816(acc[2], xa[2 * s], 0, xa[2 * s + 1], 0, b4, b5);
            mma16816(acc[3], xa[2 * s], 0, xa[2 * s + 1], 0, b6, b7);
        }
        const float v0 = (g & 2) ? ((g & 1) ? acc[3][0] : acc[2][0]) : ((g & 1) ? acc[1][0] : acc[0][0]);
        const float v1 = (g & 2) ? ((g & 1) ? acc[3][1] : acc[2][1]) : ((g & 1) ? acc[1][1] : acc[0][1]);
        if (lane < 16) mb_put2f(mb + o1, v0, v1);
        __syncwarp();
        if (lane == 0) mbar_arrive(BAR(G_P1));
    }
    asm volatile("bar.arrive 13, 384;" ::: "memory");
    if (tid == 0) TRACE(1);
    mb_st2(g_mb + o3, 0u, 0u); mb_st2(g_mb + o3 + 1024, 0u, 0u); mb_st2(g_mb + o3 + 524288, 0u, 0u); mb_st2(g_mb + o3 + 524288 + 1024, 0u, 0u);
    if (a4) mb_clear2(o4);
    if (am) { mb_clear2(om); mb_clear2(om + 8 * NC_MAX * 32); }
    if (full) {
        if (lane < 4) mb_clear2(o5);
        if (a6) mb_clear2(o6);
    }
    bar_sync(7, 416);
    if (tid == 0) TRACE(2);
    qabs_unit(SB, mb + o2a, warp, (ua >> 6) != hA, BAR(g_uk + (warp >> 1)), lane);
    if (tid == 0) TRACE(3);
    asm volatile("bar.arrive 6, 416;" ::: "memory");
    asm volatile("barrier.cluster.wait.acquire.aligned;" ::: "memory");
    {
        float acc[4][4] = {};
        float mr0 = -INFINITY, mr1 = -INFINITY, tl[4] = {};
        const int prow = (lane & 7) + (lane & 8), pch = (warp & 1) * 4 + (lane >> 4);
        const uint32_t p_src0 = SB + OFF_CKV + (warp >> 1) * 2048 + prow * 128 + ((pch ^ (prow & 7)) << 4);
        const uint32_t p_src1 = SB + OFF_CKV + (warp >> 1) * 2048 + prow * 128 + (((pch + 2) ^ (prow & 7)) << 4);
        const uint32_t one = 0x3f803f80u;
#pragma unroll 1
        for (int b = 0, pb = 0, pph = 0; b < nb; b++) {
            const bool two = 2 * b + 1 < nk;
            const uint32_t pbase = SB + p_off(pb);
            mbar_wait_cl(BAR(B_P0 + pb), pph);
            if (tid == 0) TRACE(21 + b);
            uint32_t b0[8], b1[8];
            const float mb0 = __uint_as_float(lds32(pbase + 1024 + g * 4));
            const float mb1 = __uint_as_float(lds32(pbase + 1024 + 32 + g * 4));
            const uint4 p0 = lds128(pbase + lane * 16);
            ldsm4t(p_src0 + 2 * b * UNIT, b0[0], b0[1], b0[2], b0[3]);
            ldsm4t(p_src1 + 2 * b * UNIT, b0[4], b0[5], b0[6], b0[7]);
            uint4 p1;
            if (two) {
                p1 = lds128(pbase + 512 + lane * 16);
                ldsm4t(p_src0 + (2 * b + 1) * UNIT, b1[0], b1[1], b1[2], b1[3]);
                ldsm4t(p_src1 + (2 * b + 1) * UNIT, b1[4], b1[5], b1[6], b1[7]);
            }
            if (__any_sync(~0u, mb0 != mr0 || mb1 != mr1)) {
                const float al0 = ex2(mr0 - mb0), al1 = ex2(mr1 - mb1);
                mr0 = mb0; mr1 = mb1;
#pragma unroll
                for (int i = 0; i < 4; i++) { acc[i][0] *= al0; acc[i][1] *= al0; acc[i][2] *= al1; acc[i][3] *= al1; }
                tl[0] *= al0; tl[2] *= al1;
            }
#pragma unroll
            for (int i = 0; i < 4; i++) mma16816(acc[i], p0.x, p0.y, p0.z, p0.w, b0[2 * i], b0[2 * i + 1]);
            mma16816(tl, p0.x, p0.y, p0.z, p0.w, one, one);
            if (two) {
#pragma unroll
                for (int i = 0; i < 4; i++) mma16816(acc[i], p1.x, p1.y, p1.z, p1.w, b1[2 * i], b1[2 * i + 1]);
                mma16816(tl, p1.x, p1.y, p1.z, p1.w, one, one);
            }
            if (tid == 0 && b + RP < nb) mbar_expect(BAR(B_P0 + pb), (2 * (b + RP) + 1 < nk) ? 1088 : 576);
            __syncwarp();
            if (lane == 0) red_add_rel(SB + OFF_PVC + b * 4, 1);
            if (++pb == RP) { pb = 0; pph ^= 1; }
        }
        if (am) {
            mb_put2f(mb + om, mr0, tl[0]);
            mb_put2f(mb + om + 8 * NC_MAX * 32, mr1, tl[2]);
        }
        mb_put2(g_mb + o3, pack2(acc[0][0], acc[0][1]), pack2(acc[1][0], acc[1][1]));
        mb_put2(g_mb + o3 + 1024, pack2(acc[2][0], acc[2][1]), pack2(acc[3][0], acc[3][1]));
        mb_put2(g_mb + o3 + 524288, pack2(acc[0][2], acc[0][3]), pack2(acc[1][2], acc[1][3]));
        mb_put2(g_mb + o3 + 524288 + 1024, pack2(acc[2][2], acc[2][3]), pack2(acc[3][2], acc[3][3]));
    }
    if (tid == 0) TRACE(5);
    {
        const uint32_t tpub = clock();
        const unsigned char* psrc = g_mb + MB3 + ua * 1024 + lane * 16;
        const int pn = (16 + (lane >> 1) < NC) ? 2 : 1;
        bar_sync(5, 352);
        uint32_t wb[9][8];
        const int p = (lane & 7) + (lane & 8);
        const int prow = ((p >> 1) & 1) * 8 + (p >> 2) * 2 + (p & 1), pch = (warp & 1) * 4 + (lane >> 4);
        const uint32_t src0 = SB + OFF_WA + (warp >> 1) * 2048 + prow * 128 + ((pch ^ (prow & 7)) << 4);
        const uint32_t src1 = SB + OFF_WA + (warp >> 1) * 2048 + prow * 128 + (((pch + 2) ^ (prow & 7)) << 4);
        uint4 pv[2];
#pragma unroll
        for (int ul = 0; ul < 9; ul++) {
            const uint32_t uo = (ul < 8 || nu > 8) ? ul * UNIT : 0;
            if ((ul & 1) == 0 && ul < 8) mbar_wait(BAR(g_uv + (ul >> 1)), 0);
            ldsm4t(src0 + uo, wb[ul][0], wb[ul][1], wb[ul][2], wb[ul][3]);
            ldsm4t(src1 + uo, wb[ul][4], wb[ul][5], wb[ul][6], wb[ul][7]);
        }
        while (clock() - tpub < ((P.dly >> 10) & 31) * 64) {}
        mb_first<2, 512>(psrc, pn, pv);
        if (tid == 0) TRACE(18);
        const int nA = (hA + 1) * 64 - u0;
        combine_unit(SB, psrc, pn, pv, warp, warp < nA, lane);
        bar_sync(3, 288);
        if (tid == 0) TRACE(6);
        float acc[2][4][4] = {};
#pragma unroll
        for (int ul = 0; ul < 9; ul++) {
            const uint4 a = lds128((ul < nA) == (g < 4) ? SB + OFF_AFR + ul * 64 + t * 16 : SB + OFF_PVC + 48);
#pragma unroll
            for (int i = 0; i < 4; i++) mma16816(acc[ul & 1][i], a.x, a.y, a.z, a.w, wb[ul][2 * i], wb[ul][2 * i + 1]);
        }
        float v0, v1;
        {
            const int i = g & 3;
            float e[4][2];
#pragma unroll
            for (int k = 0; k < 4; k++) {
                e[k][0] = (acc[0][k][0] + acc[0][k][2]) + (acc[1][k][0] + acc[1][k][2]);
                e[k][1] = (acc[0][k][1] + acc[0][k][3]) + (acc[1][k][1] + acc[1][k][3]);
            }
            v0 = (i & 2) ? ((i & 1) ? e[3][0] : e[2][0]) : ((i & 1) ? e[1][0] : e[0][0]);
            v1 = (i & 2) ? ((i & 1) ? e[3][1] : e[2][1]) : ((i & 1) ? e[1][1] : e[0][1]);
        }
        if (a4) mb_put2f(mb + o4, v0, v1);
        reset_unit(psrc, pn);
    }
    if (tid == 0) TRACE(7);
    if (!full) return;
    asm volatile("bar.arrive 10, 320;" ::: "memory");

    {
        mbar_wait(BAR(g_wo), 0);
        mbar_wait(BAR(g_wo + 1), 0);
        uint32_t b[8][4];
        const uint32_t src = SB + OFF_CKV + lane * 128 + ((warp ^ (lane & 7)) << 4);
#pragma unroll
        for (int s2 = 0; s2 < 8; s2++) ldsm4t(src + s2 * 4096, b[s2][0], b[s2][1], b[s2][2], b[s2][3]);
        bar_sync(8, 320);
        if (tid == 0) TRACE(8);
        float c[4][4] = {};
#pragma unroll
        for (int s2 = 0; s2 < 8; s2++) {
            const uint4 a = lds128(SB + OFF_CTX + s2 * 64 + t * 16);
            mma16816(c[(s2 & 1) * 2], a.x, 0, a.y, 0, b[s2][0], b[s2][1]);
            mma16816(c[(s2 & 1) * 2 + 1], a.z, 0, a.w, 0, b[s2][2], b[s2][3]);
        }
        if (lane < 4) mb_put2f(mb + o5, (c[0][0] + c[1][0]) + (c[2][0] + c[3][0]), (c[0][1] + c[1][1]) + (c[2][1] + c[3][1]));
    }
    asm volatile("bar.arrive 11, 288;" ::: "memory");
    if (tid == 0) TRACE(9);

    {
        mbar_wait(BAR(g_gu), 0);
        mbar_wait(BAR(g_gu + 1), 0);
        uint32_t b[7][4];
        const uint32_t src = SB + OFF_CKV + 4 * UNIT + lane * 128 + ((warp ^ (lane & 7)) << 4);
#pragma unroll
        for (int s2 = 0; s2 < 7; s2++) ldsm4t(src + s2 * 4096, b[s2][0], b[s2][1], b[s2][2], b[s2][3]);
        const uint32_t gdst = mapa(SB + OFF_GU + r * 512 + (warp * 4 + t) * 16, g & 3), gbar = mapa(BAR(B_GU), g & 3);
        mbar_wait_cl(BAR(B_H), 0);
        if (tid == 0) TRACE(10);
        float c[4][4] = {};
        const uint32_t one = 0x3f803f80u;
#pragma unroll
        for (int s2 = 0; s2 < 7; s2++) {
            const uint4 a = lds128(SB + OFF_H + (r >> 1) * 448 + s2 * 64 + t * 16);
            mma16816(c[(s2 & 1) * 2], a.x, one, a.y, one, b[s2][0], b[s2][1]);
            mma16816(c[(s2 & 1) * 2 + 1], a.z, one, a.w, one, b[s2][2], b[s2][3]);
        }
        if (g < 4)
            st_async_v4(gdst, __float_as_uint((c[0][0] + c[1][0]) + (c[2][0] + c[3][0])),
                        __float_as_uint((c[0][1] + c[1][1]) + (c[2][1] + c[3][1])), __float_as_uint((c[0][2] + c[1][2]) + (c[2][2] + c[3][2])),
                        __float_as_uint((c[0][3] + c[1][3]) + (c[2][3] + c[3][3])), gbar);
    }
    {
        mbar_wait(BAR(g_wd), 0);
        uint32_t b[4][4];
        const uint32_t src = SB + OFF_CKV + 8 * UNIT + lane * 128 + ((warp ^ (lane & 7)) << 4);
        ldsm4t(src, b[0][0], b[0][1], b[0][2], b[0][3]);
        ldsm4t(src + 4096, b[1][0], b[1][1], b[1][2], b[1][3]);
        ldsm4t(src + UNIT, b[2][0], b[2][1], b[2][2], b[2][3]);
        ldsm4t(src + UNIT + 4096, b[3][0], b[3][1], b[3][2], b[3][3]);
        mbar_wait_cl(BAR(B_GU), 0);
        if (tid == 0) TRACE(11);
        const uint32_t ga = SB + OFF_GU + (((g & 3) * 2 + (g >> 2)) * 4 + t) * 16;
        const uint4 p0 = lds128(ga), p1 = lds128(ga + 512), p2 = lds128(ga + 1024), p3 = lds128(ga + 1536);
        const float mean = __uint_as_float(lds32(SB + OFF_MISC + 8)), inv = __uint_as_float(lds32(SB + OFF_MISC + 12));
        const float g0 = bf16r(((__uint_as_float(p0.x) + __uint_as_float(p2.x)) - mean * (__uint_as_float(p0.z) + __uint_as_float(p2.z))) * inv);
        const float g1 = bf16r(((__uint_as_float(p0.y) + __uint_as_float(p2.y)) - mean * (__uint_as_float(p0.w) + __uint_as_float(p2.w))) * inv);
        const float u0v = bf16r(((__uint_as_float(p1.x) + __uint_as_float(p3.x)) - mean * (__uint_as_float(p1.z) + __uint_as_float(p3.z))) * inv);
        const float u1v = bf16r(((__uint_as_float(p1.y) + __uint_as_float(p3.y)) - mean * (__uint_as_float(p1.w) + __uint_as_float(p3.w))) * inv);
        const float s0 = bf16r(__fdividef(1.f, 1.f + __expf(-g0))), s1 = bf16r(__fdividef(1.f, 1.f + __expf(-g1)));
        const uint32_t hw = pack2(s0 * u0v, s1 * u1v);
        uint32_t a[8];
#pragma unroll
        for (int k = 0; k < 8; k++) a[k] = __shfl_sync(~0u, hw, k * 4 + t);
        float c0[4] = {}, c1[4] = {}, c2[4] = {}, c3[4] = {};
        mma16816(c0, a[0], 0, a[4], 0, b[0][0], b[0][1]);
        mma16816(c1, a[0], 0, a[4], 0, b[2][0], b[2][1]);
        mma16816(c2, a[1], 0, a[5], 0, b[0][2], b[0][3]);
        mma16816(c3, a[1], 0, a[5], 0, b[2][2], b[2][3]);
        mma16816(c0, a[2], 0, a[6], 0, b[1][0], b[1][1]);
        mma16816(c1, a[2], 0, a[6], 0, b[3][0], b[3][1]);
        mma16816(c2, a[3], 0, a[7], 0, b[1][2], b[1][3]);
        mma16816(c3, a[3], 0, a[7], 0, b[3][2], b[3][3]);
        if (a6) mb_put2f(mb + o6, (g & 1) ? c1[0] + c3[0] : c0[0] + c2[0], (g & 1) ? c1[1] + c3[1] : c0[1] + c2[1]);
    }
    asm volatile("bar.arrive 12, 288;" ::: "memory");
    if (tid == 0) TRACE(12);
}

__device__ float f_q[4096], f_qa[16 * 1024], f_s[16 * 8192], f_cc[64 * 16 * 1024], f_ctx[4096], f_h[448], f_hh[1792];

__device__ __forceinline__ void block_ln(const float* v  , float* o  ) {
    float a[14];
    const int lane = threadIdx.x & 31;
#pragma unroll
    for (int i = 0; i < 14; i++) a[i] = v[lane + 32 * i];
    float mb, den;
    ln_stats(a, mb, den);
    for (int i = threadIdx.x; i < 448; i += blockDim.x) o[i] = bf16r(ln_apply(v[i], mb, den));
    __syncthreads();
}
__global__ void fb_q(const __nv_bfloat16* x, const __nv_bfloat16* wq) {
    __shared__ float xs[448], xn[448];
    for (int i = threadIdx.x; i < 448; i += blockDim.x) xs[i] = __bfloat162float(x[i]);
    __syncthreads();
    block_ln(xs, xn);
    const int c = blockIdx.x * blockDim.x + threadIdx.x;
    float a = 0.f;
    for (int m = 0; m < 448; m++) a += xn[m] * __bfloat162float(wq[(size_t)m * 4096 + c]);
    f_q[c] = bf16r(a);
}
__global__ void fb_qabs(const __nv_bfloat16* wuk) {
    const int row = blockIdx.x * 8 + (threadIdx.x >> 5), lane = threadIdx.x & 31;
    const int h = row & 15, c = row >> 4;
    float a = 0.f;
    for (int d = lane; d < 256; d += 32) a += f_q[h * 256 + d] * __bfloat162float(wuk[(size_t)row * 256 + d]);
    for (int o = 16; o; o >>= 1) a += __shfl_xor_sync(~0u, a, o);
    if (lane == 0) f_qa[h * 1024 + c] = a * 0.0625f;
}
__global__ void fb_scores(const __nv_bfloat16* ckv) {
    const int k = blockIdx.x * 8 + (threadIdx.x >> 5), lane = threadIdx.x & 31;
    float a[16] = {};
    for (int c = lane; c < 1024; c += 32) {
        const float v = __bfloat162float(ckv[(size_t)k * 1024 + c]);
#pragma unroll
        for (int h = 0; h < 16; h++) a[h] += v * f_qa[h * 1024 + c];
    }
#pragma unroll
    for (int h = 0; h < 16; h++) {
        for (int o = 16; o; o >>= 1) a[h] += __shfl_xor_sync(~0u, a[h], o);
        if (lane == 0) f_s[h * 8192 + k] = a[h];
    }
}
__global__ void fb_softmax() {
    __shared__ float red[32];
    float* s = f_s + blockIdx.x * 8192;
    float m = -INFINITY;
    for (int i = threadIdx.x; i < 8192; i += blockDim.x) m = fmaxf(m, s[i]);
    for (int o = 16; o; o >>= 1) m = fmaxf(m, __shfl_xor_sync(~0u, m, o));
    if ((threadIdx.x & 31) == 0) red[threadIdx.x >> 5] = m;
    __syncthreads();
    m = red[0];
    for (int i = 1; i < (int)(blockDim.x >> 5); i++) m = fmaxf(m, red[i]);
    __syncthreads();
    float l = 0.f;
    for (int i = threadIdx.x; i < 8192; i += blockDim.x) { const float e = __expf(s[i] - m); s[i] = e; l += e; }
    for (int o = 16; o; o >>= 1) l += __shfl_xor_sync(~0u, l, o);
    if ((threadIdx.x & 31) == 0) red[threadIdx.x >> 5] = l;
    __syncthreads();
    l = 0.f;
    for (int i = 0; i < (int)(blockDim.x >> 5); i++) l += red[i];
    const float inv = 1.f / l;
    for (int i = threadIdx.x; i < 8192; i += blockDim.x) s[i] *= inv;
}
__global__ void fb_pv(const __nv_bfloat16* ckv) {
    const int c = blockIdx.y * 256 + threadIdx.x, kb = blockIdx.x * 128;
    float a[16] = {};
    for (int k = kb; k < kb + 128; k++) {
        const float v = __bfloat162float(ckv[(size_t)k * 1024 + c]);
#pragma unroll
        for (int h = 0; h < 16; h++) a[h] += v * f_s[h * 8192 + k];
    }
#pragma unroll
    for (int h = 0; h < 16; h++) f_cc[(blockIdx.x * 16 + h) * 1024 + c] = a[h];
}
__global__ void fb_ctx(const __nv_bfloat16* wuv) {
    __shared__ float cc[1024];
    const int h = blockIdx.x;
    for (int c = threadIdx.x; c < 1024; c += 256) {
        float a = 0.f;
        for (int i = 0; i < 64; i++) a += f_cc[(i * 16 + h) * 1024 + c];
        cc[c] = a;
    }
    __syncthreads();
    float a = 0.f;
    for (int c = 0; c < 1024; c++) a += cc[c] * __bfloat162float(wuv[(size_t)c * 4096 + h * 256 + threadIdx.x]);
    f_ctx[h * 256 + threadIdx.x] = bf16r(a);
}
__global__ void fb_o(const __nv_bfloat16* x, const __nv_bfloat16* wo) {
    __shared__ float red[8][32];
    const int m = blockIdx.x * 32 + (threadIdx.x & 31), p = threadIdx.x >> 5;
    float a = 0.f;
    for (int i = p * 512; i < p * 512 + 512; i++) a += f_ctx[i] * __bfloat162float(wo[(size_t)i * 448 + m]);
    red[p][threadIdx.x & 31] = a;
    __syncthreads();
    if (p == 0) {
        for (int i = 1; i < 8; i++) a += red[i][threadIdx.x];
        f_h[m] = bf16r(__bfloat162float(x[m]) + bf16r(a));
    }
}
__global__ void fb_gu(const __nv_bfloat16* wg, const __nv_bfloat16* wu) {
    __shared__ float hs[448], hn[448];
    for (int i = threadIdx.x; i < 448; i += blockDim.x) hs[i] = f_h[i];
    __syncthreads();
    block_ln(hs, hn);
    const int f = blockIdx.x * 64 + threadIdx.x;
    float a = 0.f, b = 0.f;
    for (int m = 0; m < 448; m++) {
        a += hn[m] * __bfloat162float(wg[(size_t)m * 1792 + f]);
        b += hn[m] * __bfloat162float(wu[(size_t)m * 1792 + f]);
    }
    f_hh[f] = bf16r(bf16r(1.f / (1.f + __expf(-bf16r(a)))) * bf16r(b));
}
__global__ void fb_down(const __nv_bfloat16* wd, __nv_bfloat16* out) {
    __shared__ float red[8][32];
    const int m = blockIdx.x * 32 + (threadIdx.x & 31), p = threadIdx.x >> 5;
    float a = 0.f;
    for (int i = p * 224; i < p * 224 + 224; i++) a += f_hh[i] * __bfloat162float(wd[(size_t)i * 448 + m]);
    red[p][threadIdx.x & 31] = a;
    __syncthreads();
    if (p == 0) {
        for (int i = 1; i < 8; i++) a += red[i][threadIdx.x];
        out[m] = __float2bfloat16_rn(f_h[m] + bf16r(a));
    }
}

typedef CUresult (*EncodeFn)(CUtensorMap*, CUtensorMapDataType, cuuint32_t, void*, const cuuint64_t*, const cuuint64_t*,
                             const cuuint32_t*, const cuuint32_t*, CUtensorMapInterleave, CUtensorMapSwizzle,
                             CUtensorMapL2promotion, CUtensorMapFloatOOBfill);

bool encode3(EncodeFn enc, CUtensorMap* m, const void* p, uint64_t rows, uint64_t rowbytes) {
    cuuint64_t dim[3] = {64, rows, rowbytes / 128};
    cuuint64_t str[2] = {rowbytes, 128};
    cuuint32_t box[3] = {64, 16, 4}, es[3] = {1, 1, 1};
    return enc(m, CU_TENSOR_MAP_DATA_TYPE_BFLOAT16, 3, const_cast<void*>(p), dim, str, box, es, CU_TENSOR_MAP_INTERLEAVE_NONE,
               CU_TENSOR_MAP_SWIZZLE_128B, CU_TENSOR_MAP_L2_PROMOTION_NONE, CU_TENSOR_MAP_FLOAT_OOB_FILL_NONE) == CUDA_SUCCESS;
}
bool encode2(EncodeFn enc, CUtensorMap* m, const void* p, uint64_t rows, uint64_t cols, uint32_t boxrows) {
    cuuint64_t dim[2] = {cols, rows};
    cuuint64_t str[1] = {cols * 2};
    cuuint32_t box[2] = {64, boxrows}, es[2] = {1, 1};
    return enc(m, CU_TENSOR_MAP_DATA_TYPE_BFLOAT16, 2, const_cast<void*>(p), dim, str, box, es, CU_TENSOR_MAP_INTERLEAVE_NONE,
               CU_TENSOR_MAP_SWIZZLE_128B, CU_TENSOR_MAP_L2_PROMOTION_NONE, CU_TENSOR_MAP_FLOAT_OOB_FILL_NONE) == CUDA_SUCCESS;
}

int g_force_fallback = 0;
int g_force_nc = 0;
int g_window = 0x2233;
unsigned g_dly = (24u << 10) | (8u << 15);

}

extern "C" void kernel_launch(void* const* d_in, const int* in_sizes, int n_in, void* d_out, int out_size) {
    const __nv_bfloat16* x = (const __nv_bfloat16*)d_in[0];
    const __nv_bfloat16* ckv = (const __nv_bfloat16*)d_in[1];
    const __nv_bfloat16* wq = (const __nv_bfloat16*)d_in[2];
    const __nv_bfloat16* wuk = (const __nv_bfloat16*)d_in[3];
    const __nv_bfloat16* wuv = (const __nv_bfloat16*)d_in[4];
    const __nv_bfloat16* wo = (const __nv_bfloat16*)d_in[5];
    const __nv_bfloat16* wg = (const __nv_bfloat16*)d_in[7];
    const __nv_bfloat16* wu = (const __nv_bfloat16*)d_in[8];
    const __nv_bfloat16* wd = (const __nv_bfloat16*)d_in[9];
    __nv_bfloat16* out = (__nv_bfloat16*)d_out;
    cudaStream_t st = cudaStreamPerThread;

    static int s_init = 0, s_nc = 0;
    static EncodeFn s_enc = nullptr;
    cudaLaunchConfig_t cfg = {};
    cudaLaunchAttribute at[1];
    at[0].id = cudaLaunchAttributeClusterDimension;
    at[0].val.clusterDim.x = 4; at[0].val.clusterDim.y = 1; at[0].val.clusterDim.z = 1;
    cfg.blockDim = dim3(NTHR); cfg.dynamicSmemBytes = SMEM_BYTES + 128; cfg.stream = st; cfg.attrs = at; cfg.numAttrs = 1;
    if (!s_init) {
        s_init = 1;
        void* fn = nullptr;
        cudaDriverEntryPointQueryResult qr;
        if (cudaGetDriverEntryPoint("cuTensorMapEncodeTiled", &fn, cudaEnableDefault, &qr) == cudaSuccess &&
            qr == cudaDriverEntryPointSuccess)
            s_enc = (EncodeFn)fn;
        int nc = 0;
        cfg.gridDim = dim3(4 * NC_MAX);
        if (cudaFuncSetAttribute(fused_kernel, cudaFuncAttributeMaxDynamicSharedMemorySize, SMEM_BYTES + 128) == cudaSuccess &&
            cudaOccupancyMaxActiveClusters(&nc, fused_kernel, &cfg) == cudaSuccess)
            s_nc = nc > NC_MAX ? NC_MAX : nc;
        (void)cudaGetLastError();
    }
    if (g_force_nc && g_force_nc < s_nc) s_nc = g_force_nc;
    Params P;
    bool ok = s_enc != nullptr && s_nc >= NC_MIN && !g_force_fallback;
    ok = ok && encode3(s_enc, &P.wq, wq, 448, 8192) && encode3(s_enc, &P.wuk, wuk, 1024, 8192) &&
         encode3(s_enc, &P.ckv, ckv, 8192, 2048) && encode3(s_enc, &P.wuv, wuv, 1024, 8192) &&
         encode2(s_enc, &P.wo, wo, 4096, 448, 64) && encode2(s_enc, &P.wg, wg, 448, 1792, 112) &&
         encode2(s_enc, &P.wu, wu, 448, 1792, 112) && encode2(s_enc, &P.wd, wd, 1792, 448, 64);
    if (ok) {
        P.x = x; P.out = out; P.NC = s_nc; P.W = g_window; P.dly = g_dly;
        const int N = 4 * s_nc;
        int ustart[4 * NC_MAX + 1], kstart[NC_MAX + 1];
        {
            const int kbase = 512 / s_nc, kext = 512 - kbase * s_nc;
            kstart[0] = 0;
            for (int jj = 0; jj < s_nc; jj++) kstart[jj + 1] = kstart[jj] + kbase + (jj >= s_nc - kext ? 1 : 0);
            int cap = 0;
            for (int c = 0; c < N; c++) cap += (kstart[(c >> 2) + 1] - kstart[c >> 2] > 17) ? 8 : 9;
            const bool deep = cap >= 1024;
            P.RS = deep ? 5 : 3;
            int nine = 0;
            for (int c = 0; c < N; c++) nine += (!deep || kstart[(c >> 2) + 1] - kstart[c >> 2] <= 17) ? 1 : 0;
            const int uext = 1024 - 8 * N;
            ustart[0] = 0;
            for (int c = 0, i = 0; c < N; c++) {
                int extra = 0;
                if (!deep || kstart[(c >> 2) + 1] - kstart[c >> 2] <= 17) { extra = (i + 1) * uext / nine - i * uext / nine; i++; }
                ustart[c + 1] = ustart[c] + 8 + extra;
            }
        }
        auto owner = [&](int u) { int c = 0; while (ustart[c + 1] <= u) c++; return c; };
        for (int c = 0; c < 4 * NC_MAX; c++) {
            if (c >= N) { P.tab[c] = make_uint2(0, 0); continue; }
            const int jj = c >> 2, u0 = ustart[c], nu = ustart[c + 1] - u0;
            const int k0 = kstart[jj], nk = kstart[jj + 1] - k0;
            const int h7 = (c / 7) & 15, mb7 = c % 7, hA = u0 >> 6, hB = (u0 + nu - 1) >> 6;
            const int ns = owner(h7 * 64 + 63) - owner(h7 * 64) + 1;
            P.tab[c].x = u0 | (nu << 10) | (k0 << 14) | (nk << 23);
            P.tab[c].y = h7 | (mb7 << 4) | ((c - owner(hA * 64)) << 8) | ((c - owner(hB * 64)) << 12) | (ns << 16);
        }
        cfg.gridDim = dim3(4 * s_nc);
        cudaLaunchKernelEx(&cfg, fused_kernel, P);
        return;
    }
    fb_q<<<16, 256, 0, st>>>(x, wq);
    fb_qabs<<<2048, 256, 0, st>>>(wuk);
    fb_scores<<<1024, 256, 0, st>>>(ckv);
    fb_softmax<<<16, 1024, 0, st>>>();
    fb_pv<<<dim3(64, 4), 256, 0, st>>>(ckv);
    fb_ctx<<<16, 256, 0, st>>>(wuv);
    fb_o<<<14, 256, 0, st>>>(x, wo);
    fb_gu<<<28, 64, 0, st>>>(wg, wu);
    fb_down<<<14, 256, 0, st>>>(wd, out);
}
```
